```python
import torch

def _softmax(x, axis=-1):
    return torch.softmax(x, dim=axis)
def _gelu(x):
    return torch.nn.functional.gelu(x, approximate="tanh")
def _silu(x):
    return torch.nn.functional.silu(x)
def _sigmoid(x):
    return torch.sigmoid(x)
def _layernorm(x, axis=-1, eps=1e-5):
    m = x.mean(dim=axis, keepdim=True)
    v = x.var(dim=axis, keepdim=True, unbiased=False)
    return (x - m) / torch.sqrt(v + eps)
def _scatter_add(tgt, idx, src, axis=0):
    return tgt.clone().index_add_(axis, idx, src)
def _segment_sum(src, seg, n):
    out = torch.zeros((n,) + src.shape[1:], dtype=src.dtype)
    return out.index_add_(0, seg, src)
def _pad(x, pw):
    flat = tuple(v for pair in reversed(pw) for v in pair)
    return torch.nn.functional.pad(x, flat)

kernel_name = 'standalone__gqa_softmax__near_ridge'

def setup_inputs():

    _w = (lambda a: (lambda t: t.to(torch.bfloat16) if t.is_floating_point() else t)(torch.as_tensor(a)))
    B, Hq, Hkv, Sq, Sk, D = 16, 16, 8, 192, 512, 256
    return {
        "q": _w((lambda *s: torch.randn(*s, dtype=torch.bfloat16) * 0.8)(B, Hq, Sq, D)),
        "k": _w((lambda *s: torch.randn(*s, dtype=torch.bfloat16) * 0.8)(B, Hkv, Sk, D)),
        "v": _w((lambda *s: torch.randn(*s, dtype=torch.bfloat16) * 0.05)(B, Hkv, Sk, D)),
    }

def reference(q, k, v):
    B, Hq, Sq, D = q.shape
    Hkv = k.shape[1]
    rep = Hq // Hkv
    k = (lambda x, n, axis: torch.repeat_interleave(x, n, dim=axis))(k, rep, axis=1)
    v = (lambda x, n, axis: torch.repeat_interleave(x, n, dim=axis))(v, rep, axis=1)
    scale = D ** -0.5
    scores = torch.einsum("bhqd,bhkd->bhqk", q, k) * scale
    p = _softmax(scores, axis=-1)
    return torch.einsum("bhqk,bhkd->bhqd", p, v)
```

```cpp
#include <cuda.h>
#include <cuda_bf16.h>
#include <cuda_runtime.h>
#include <stdint.h>

#define PRE_CHUNKS 2
#define SPEC 16
#define TURN2 1
#define KVPOL 7
#define LATE 8000
#define PROL 0
#define Q1POS 4
#define SYNC3 -1
#define PREG "24"
#define CREG "240"
#define STAG 2000
#define TSMASK 0xff

namespace {

constexpr int kD = 256;
constexpr int kSk = 512;
constexpr int kRowsPerHead = 384;
constexpr int kHeads = 128;
constexpr int kTriples = 44;
constexpr int kGrid = 3 * kTriples;
constexpr int kThreads = 384;
constexpr int kTilesKV = 4;

constexpr int kChunk = 16384;
constexpr int kOffK = 0;
constexpr int kOffV = 65536;
constexpr int kOffX = 131072;
constexpr int kOffBar = 229376;
constexpr int kSmemBytes = kOffBar + 256;

constexpr int kBarKFull = 0, kBarKEmpty = 4, kBarVFull = 8, kBarVEmpty = 12;
constexpr int kBarQFull = 16, kBarQEmpty = 18, kBarXFree = 20;

constexpr uint32_t kSyncPeriod = 128;
__device__ uint32_t g_sync[kTriples * 32];

#define TSR(k) do {} while (0)
#define TSFLUSH(it) do {} while (0)
#define TS(i) do {} while (0)
#define TSG(i) do {} while (0)

__device__ __forceinline__ uint32_t smem_u32(const void* p) { return (uint32_t)__cvta_generic_to_shared(p); }

__device__ __forceinline__ void mbar_init(uint32_t bar, uint32_t cnt) {
    asm volatile("mbarrier.init.shared::cta.b64 [%0], %1;" ::"r"(bar), "r"(cnt) : "memory");
}
__device__ __forceinline__ void mbar_expect_tx(uint32_t bar, uint32_t bytes) {
    asm volatile("mbarrier.arrive.expect_tx.shared::cta.b64 _, [%0], %1;" ::"r"(bar), "r"(bytes) : "memory");
}
__device__ __forceinline__ void mbar_arrive(uint32_t bar) {
    asm volatile("mbarrier.arrive.shared::cta.b64 _, [%0];" ::"r"(bar) : "memory");
}
__device__ __forceinline__ void mbar_wait(uint32_t bar, uint32_t parity) {
    asm volatile(
        "{\n"
        ".reg .pred p;\n"
        ".reg .u32 n;\n"
        "mbarrier.try_wait.parity.shared::cta.b64 p, [%0], %1;\n"
        "@p bra DONE_%=;\n"
        "mov.u32 n, 0;\n"
        "LOOP_%=:\n"
        "mbarrier.try_wait.parity.shared::cta.b64 p, [%0], %1;\n"
        "@p bra DONE_%=;\n"
        "add.u32 n, n, 1;\n"
        "setp.lt.u32 p, n, 0x400000;\n"
        "@p bra LOOP_%=;\n"
        "trap;\n"
        "DONE_%=:\n"
        "}\n" ::"r"(bar), "r"(parity) : "memory");
}
__device__ __forceinline__ void tma_load3(uint32_t dst, const CUtensorMap* map, uint32_t bar, int c0, int c1, int c2) {
    asm volatile(
        "cp.async.bulk.tensor.3d.shared::cluster.global.mbarrier::complete_tx::bytes [%0], [%1, {%3, %4, %5}], [%2];"
        ::"r"(dst), "l"(map), "r"(bar), "r"(c0), "r"(c1), "r"(c2) : "memory");
}
__device__ __forceinline__ void tma_load3_hint(uint32_t dst, const CUtensorMap* map, uint32_t bar, int c0, int c1, int c2, uint64_t pol) {
    asm volatile(
        "cp.async.bulk.tensor.3d.shared::cluster.global.mbarrier::complete_tx::bytes.L2::cache_hint [%0], [%1, {%3, %4, %5}], [%2], %6;"
        ::"r"(dst), "l"(map), "r"(bar), "r"(c0), "r"(c1), "r"(c2), "l"(pol) : "memory");
}
__device__ __forceinline__ void tma_store3(const CUtensorMap* map, uint32_t src, int c0, int c1, int c2) {
    asm volatile("cp.async.bulk.tensor.3d.global.shared::cta.bulk_group [%0, {%2, %3, %4}], [%1];"
                 ::"l"(map), "r"(src), "r"(c0), "r"(c1), "r"(c2) : "memory");
}
__device__ __forceinline__ void bar_sync(int id, int n) { asm volatile("bar.sync %0, %1;" ::"r"(id), "r"(n) : "memory"); }
__device__ __forceinline__ void bar_arrive(int id, int n) { asm volatile("bar.arrive %0, %1;" ::"r"(id), "r"(n) : "memory"); }

__device__ __forceinline__ void wgmma_fence() { asm volatile("wgmma.fence.sync.aligned;" ::: "memory"); }
__device__ __forceinline__ void wgmma_commit() { asm volatile("wgmma.commit_group.sync.aligned;" ::: "memory"); }
template <int N> __device__ __forceinline__ void wgmma_wait() { asm volatile("wgmma.wait_group.sync.aligned %0;" ::"n"(N) : "memory"); }

template <int N> __device__ __forceinline__ void reg_fence(float (&r)[N]) {
#pragma unroll
    for (int i = 0; i < N; i++) asm volatile("" : "+f"(r[i])::"memory");
}
template <int N> __device__ __forceinline__ void reg_fence(uint32_t (&r)[N]) {
#pragma unroll
    for (int i = 0; i < N; i++) asm volatile("" : "+r"(r[i])::"memory");
}

__device__ __forceinline__ uint64_t make_desc(uint32_t addr, uint32_t lbo, uint32_t sbo) {
    return (uint64_t)((addr & 0x3FFFF) >> 4) | ((uint64_t)(lbo >> 4) << 16) | ((uint64_t)(sbo >> 4) << 32) | (1ull << 62);
}

#define F8(a, i) "+f"(a[i]), "+f"(a[i + 1]), "+f"(a[i + 2]), "+f"(a[i + 3]), "+f"(a[i + 4]), "+f"(a[i + 5]), "+f"(a[i + 6]), "+f"(a[i + 7])
#define F32(a, i) F8(a, i), F8(a, i + 8), F8(a, i + 16), F8(a, i + 24)

__device__ __forceinline__ void wgmma_qk(float (&d)[64], uint64_t da, uint64_t db, int scale_d) {
    asm volatile(
        "{\n.reg .pred p;\nsetp.ne.b32 p, %66, 0;\n"
        "wgmma.mma_async.sync.aligned.m64n128k16.f32.bf16.bf16 "
        "{%0, %1, %2, %3, %4, %5, %6, %7, %8, %9, %10, %11, %12, %13, %14, %15, "
        "%16, %17, %18, %19, %20, %21, %22, %23, %24, %25, %26, %27, %28, %29, %30, %31, "
        "%32, %33, %34, %35, %36, %37, %38, %39, %40, %41, %42, %43, %44, %45, %46, %47, "
        "%48, %49, %50, %51, %52, %53, %54, %55, %56, %57, %58, %59, %60, %61, %62, %63}, "
        "%64, %65, p, 1, 1, 0, 0;\n}\n"
        : F32(d, 0), F32(d, 32)
        : "l"(da), "l"(db), "r"(scale_d));
}
__device__ __forceinline__ void wgmma_pv(float (&d)[128], uint32_t a0, uint32_t a1, uint32_t a2, uint32_t a3, uint64_t db, int scale_d) {
    asm volatile(
        "{\n.reg .pred p;\nsetp.ne.b32 p, %133, 0;\n"
        "wgmma.mma_async.sync.aligned.m64n256k16.f32.bf16.bf16 "
        "{%0, %1, %2, %3, %4, %5, %6, %7, %8, %9, %10, %11, %12, %13, %14, %15, "
        "%16, %17, %18, %19, %20, %21, %22, %23, %24, %25, %26, %27, %28, %29, %30, %31, "
        "%32, %33, %34, %35, %36, %37, %38, %39, %40, %41, %42, %43, %44, %45, %46, %47, "
        "%48, %49, %50, %51, %52, %53, %54, %55, %56, %57, %58, %59, %60, %61, %62, %63, "
        "%64, %65, %66, %67, %68, %69, %70, %71, %72, %73, %74, %75, %76, %77, %78, %79, "
        "%80, %81, %82, %83, %84, %85, %86, %87, %88, %89, %90, %91, %92, %93, %94, %95, "
        "%96, %97, %98, %99, %100, %101, %102, %103, %104, %105, %106, %107, %108, %109, %110, %111, "
        "%112, %113, %114, %115, %116, %117, %118, %119, %120, %121, %122, %123, %124, %125, %126, %127}, "
        "{%128, %129, %130, %131}, %132, p, 1, 1, 1;\n}\n"
        : F32(d, 0), F32(d, 32), F32(d, 64), F32(d, 96)
        : "r"(a0), "r"(a1), "r"(a2), "r"(a3), "l"(db), "r"(scale_d));
}

__device__ __forceinline__ void breathe() { asm volatile("pmevent 0;" ::: "memory"); }
template <int N> __device__ __forceinline__ void pin(float* r) {
#pragma unroll
    for (int i = 0; i < N; i++) asm volatile("" : "+f"(r[i])::"memory");
}

__device__ __forceinline__ float ex2(float x) {
    float y;
    asm("ex2.approx.ftz.f32 %0, %1;" : "=f"(y) : "f"(x));
    return y;
}
__device__ __forceinline__ uint32_t pack_bf16(float lo, float hi) {
    uint32_t r;
    asm("cvt.rn.bf16x2.f32 %0, %1, %2;" : "=r"(r) : "f"(hi), "f"(lo));
    return r;
}

__device__ __forceinline__ uint32_t clock32() {
    uint32_t c;
    asm volatile("mov.u32 %0, %%clock;" : "=r"(c));
    return c;
}
__device__ __forceinline__ void spin(uint32_t cycles) {
    const uint32_t t0 = clock32();
    while (clock32() - t0 < cycles) __nanosleep(32);
}

__global__ void __launch_bounds__(kThreads, 1)
gqa_attn_kernel(const __grid_constant__ CUtensorMap tmQ, const __grid_constant__ CUtensorMap tmK,
                const __grid_constant__ CUtensorMap tmV, const __grid_constant__ CUtensorMap tmO,
                const __grid_constant__ CUtensorMap tmQ8) {
    extern __shared__ __align__(1024) uint8_t smem[];
    const uint32_t sbase = smem_u32(smem);
    const uint32_t bars = sbase + kOffBar;
    auto BAR = [&](int i) { return bars + 8u * i; };

    const int warp = __shfl_sync(0xffffffffu, threadIdx.x >> 5, 0);
    const int lane = threadIdx.x & 31;
    const int triple = blockIdx.x / 3;
    const int sub = blockIdx.x - 3 * triple;
    const int head0 = kTriples - 1 - triple;
    const int nrounds = (head0 + 2 * kTriples < kHeads) ? 3 : 2;
    auto XBUF = [&](int r, int k) { return sbase + kOffX + ((3 - r + k) % 3) * 32768u; };

    uint64_t pol;
    asm volatile("createpolicy.fractional.L2::evict_first.b64 %0, 1.0;" : "=l"(pol));
    auto load_kv = [&](int r, int j, int c) {
        const int krow = (head0 + r * kTriples) * kSk + j * 128;
        const uint32_t f = BAR(c < 4 ? kBarKFull + c : kBarVFull + c - 4);
        mbar_expect_tx(f, kChunk);
        if ((KVPOL >> (r + 3 - nrounds)) & 1) {
            if (c < 4) tma_load3_hint(sbase + kOffK + c * kChunk, &tmK, f, 0, krow, c, pol);
            else tma_load3_hint(sbase + kOffV + (c - 4) * kChunk, &tmV, f, 0, krow + (c - 4) * 32, 0, pol);
        } else {
            if (c < 4) tma_load3(sbase + kOffK + c * kChunk, &tmK, f, 0, krow, c);
            else tma_load3(sbase + kOffV + (c - 4) * kChunk, &tmV, f, 0, krow + (c - 4) * 32, 0);
        }
    };
    auto load_q = [&](int r, int w, int g) {
        const int qrow = (head0 + r * kTriples) * kRowsPerHead + sub * 128 + w * 64 + g * 8;
        tma_load3_hint(XBUF(r, w) + g * 4096, &tmQ, BAR(kBarQFull + w), 0, qrow, 0, pol);
    };

    auto load_q8 = [&](int r, int w) {
        const int qgrp = ((head0 + r * kTriples) * kRowsPerHead + sub * 128 + w * 64) / 8;
        asm volatile(
            "cp.async.bulk.tensor.4d.shared::cluster.global.mbarrier::complete_tx::bytes.L2::cache_hint [%0], [%1, {%3, %3, %3, %4}], [%2], %5;"
            ::"r"(XBUF(r, w)), "l"(&tmQ8), "r"(BAR(kBarQFull + w)), "r"(0), "r"(qgrp), "l"(pol) : "memory");
    };

    if (threadIdx.x == 256) {
#pragma unroll
        for (int i = 0; i < 4; i++) {
            mbar_init(BAR(kBarKFull + i), 1);
            mbar_init(BAR(kBarKEmpty + i), 8);
            mbar_init(BAR(kBarVFull + i), 1);
            mbar_init(BAR(kBarVEmpty + i), 8);
        }
#pragma unroll
        for (int i = 0; i < 2; i++) {
            mbar_init(BAR(kBarQFull + i), 1);
            mbar_init(BAR(kBarQEmpty + i), 4);
        }
        mbar_init(BAR(kBarXFree), 8);
        asm volatile("fence.mbarrier_init.release.cluster;" ::: "memory");
        if (LATE && nrounds == 2) spin(LATE);
        if (STAG && nrounds == 3) spin(((head0 * 17) % 40) * (STAG / 40));
        load_kv(0, 0, 0);
        mbar_expect_tx(BAR(kBarQFull), 32768);
        load_q8(0, 0);
    }
    __syncthreads();

    if (warp >= 8) {
        asm volatile("setmaxnreg.dec.sync.aligned.u32 " PREG ";");
        if (threadIdx.x == 256) {
            uint32_t* const cnt = g_sync + triple * 32;
            uint32_t want = 0;
            int it = 0;
            for (int r = 0; r < nrounds; r++) {
                for (int j = 0; j < kTilesKV; j++, it++) {
                    const uint32_t par = (it & 1) ^ 1;
                    const bool nextq = j >= 2 && r + 1 < nrounds;
                    if (nextq && j == 2) {
                        mbar_wait(BAR(kBarXFree), (r & 1) ^ 1);
                        mbar_expect_tx(BAR(kBarQFull), 32768);
                    }
#pragma unroll
                    for (int c = 0; c < 8; c++) {
                        if (j == 0 && c == Q1POS) {
                            mbar_wait(BAR(kBarQEmpty), (r & 1) ^ 1);
                            mbar_expect_tx(BAR(kBarQFull + 1), 32768);
                            load_q8(r, 1);
                        }
                        if (it == 0 && c == 0) continue;
                        if (PROL >= 1 && it == 0 && c == 4) mbar_wait(BAR(kBarKFull), 0);
                        if (SYNC3 >= 0 && (c & 3) == 0 && (it > 1 || (it == 1 && c == 4))) {
                            for (int n = 0; n < 64; n++) {
                                uint32_t v;
                                asm volatile("ld.relaxed.gpu.global.u32 %0, [%1];" : "=r"(v) : "l"(cnt) : "memory");
                                if ((int)(v - want) >= 0) break;
                            }
                        }
                        mbar_wait(BAR(c < 4 ? kBarKEmpty + c : kBarVEmpty + c - 4), par);
                        load_kv(r, j, c);
                        if (nextq && (c & 1)) load_q(r + 1, 0, (j - 2) * 4 + (c >> 1));
                        if (SYNC3 >= 0 && it == 0 && c == 7) {
                            asm volatile("ld.relaxed.gpu.global.u32 %0, [%1];" : "=r"(want) : "l"(cnt) : "memory");
                            want &= ~(kSyncPeriod - 1);
                        }
                        if (SYNC3 >= 0 && it > 0 && (c & 3) == SYNC3) {
                            asm volatile("red.relaxed.gpu.global.add.u32 [%0], %1;" ::"l"(cnt), "r"(1u) : "memory");
                            want += 3;
                        }
                    }
                }
            }
            if (SYNC3 >= 0 && sub == 0)
                asm volatile("red.relaxed.gpu.global.add.u32 [%0], %1;" ::"l"(cnt), "r"(kSyncPeriod - 3 * (8 * nrounds - 2)) : "memory");
        }
    } else {
        asm volatile("setmaxnreg.inc.sync.aligned.u32 " CREG ";");
        const int wg = warp >> 2;
        const float kScale = 0.0625f * 1.4426950408889634f;

        const uint64_t descK = make_desc(sbase + kOffK, 16, 1024);
        const uint64_t descV = make_desc(sbase + kOffV, 4096, 1024);

        float o[128];
        float s[64];
        uint32_t p[32];
        float m0, m1, l0, l1, i1;
        auto stage_o = [&](uint32_t slot, int r, int h, float inv) {
            const uint32_t addr = slot + (lane & 7) * 128;
#pragma unroll
            for (int b = 0; b < 32; b += 4) {
                const uint32_t r0 = pack_bf16(o[b * 4 + 2 * h] * inv, o[b * 4 + 2 * h + 1] * inv);
                const uint32_t r1 = pack_bf16(o[b * 4 + 4 + 2 * h] * inv, o[b * 4 + 5 + 2 * h] * inv);
                const uint32_t r2 = pack_bf16(o[b * 4 + 8 + 2 * h] * inv, o[b * 4 + 9 + 2 * h] * inv);
                const uint32_t r3 = pack_bf16(o[b * 4 + 12 + 2 * h] * inv, o[b * 4 + 13 + 2 * h] * inv);
                asm volatile("stmatrix.sync.aligned.m8n8.x4.shared.b16 [%0], {%1, %2, %3, %4};"
                             ::"r"(addr + (b >> 3) * 1024 + ((((b & 7) + (lane >> 3)) ^ (lane & 7)) << 4)),
                               "r"(r0), "r"(r1), "r"(r2), "r"(r3) : "memory");
                if (b & 4) breathe();
            }
            asm volatile("fence.proxy.async.shared::cta;" ::: "memory");
            __syncwarp();
            if (lane == 0) {
                tma_store3(&tmO, slot, 0, (head0 + r * kTriples) * kRowsPerHead + sub * 128 + warp * 16 + h * 8, 0);
                asm volatile("cp.async.bulk.commit_group;" ::: "memory");
            }
        };

        if (TURN2 && wg == 1) bar_arrive(1, 256);
        TS(124);
        int it = 0;
        for (int r = 0; r < nrounds; r++) {
            const uint64_t descQ = make_desc(XBUF(r, wg), 16, 4096);
            mbar_wait(BAR(kBarQFull + wg), r & 1);
            l0 = l1 = 0.f;
#pragma unroll 1
            for (int j = 0; j < kTilesKV; j++, it++) {
                const uint32_t par = it & 1;
                TSR(1);
                if (TURN2 || wg == 1) bar_sync(1 + wg, 256);
#pragma unroll
                for (int c = 0; c < 4; c++) {
                    mbar_wait(BAR(kBarKFull + c), par);
                    wgmma_fence();
#pragma unroll
                    for (int k = 0; k < 4; k++)
                        wgmma_qk(s, descQ + (c * 1024 + k * 32) / 16, descK + (c * kChunk + k * 32) / 16, (c | k) != 0);
                    wgmma_commit();
                    if (c == 2) {
                        wgmma_wait<2>();
                        if (lane == 0) mbar_arrive(BAR(kBarKEmpty + 0));
                    }
                }
                if (wg == 0) bar_arrive(2, 256);
                TSR(3);
                wgmma_wait<2>();
                if (lane == 0) mbar_arrive(BAR(kBarKEmpty + 1));
                if (j == 0 && r > 0) {
                    asm volatile("cp.async.bulk.wait_group.read 0;" ::: "memory");
                    __syncwarp();
                    stage_o(XBUF(r - 1, 1) + warp * 4096, r - 1, 1, i1);
                }
                TSR(7);
                wgmma_wait<1>();
                if (lane == 0) mbar_arrive(BAR(kBarKEmpty + 2));
                wgmma_wait<0>();
                if (lane == 0) mbar_arrive(BAR(kBarKEmpty + 3));
                if (lane == 0 && j == kTilesKV - 1) mbar_arrive(BAR(kBarQEmpty + wg));
                reg_fence(s);
                TSR(2);

                auto rowmax = [&](float& mx0, float& mx1) {
                    mx0 = fmaxf(s[0], s[1]);
                    mx1 = fmaxf(s[2], s[3]);
#pragma unroll
                    for (int i = 4; i < 64; i += 4) {
                        mx0 = fmaxf(mx0, fmaxf(s[i], s[i + 1]));
                        mx1 = fmaxf(mx1, fmaxf(s[i + 2], s[i + 3]));
                    }
                    mx0 = fmaxf(mx0, __shfl_xor_sync(0xffffffffu, mx0, 1));
                    mx1 = fmaxf(mx1, __shfl_xor_sync(0xffffffffu, mx1, 1));
                    mx0 = fmaxf(mx0, __shfl_xor_sync(0xffffffffu, mx0, 2));
                    mx1 = fmaxf(mx1, __shfl_xor_sync(0xffffffffu, mx1, 2));
                };
                if (j == 0) {
                    float mx0, mx1;
                    rowmax(mx0, mx1);
                    m0 = mx0 * kScale;
                    m1 = mx1 * kScale;
                }
                float e[SPEC ? SPEC : 1];
                {
                    int c0 = 0, c1 = 0;
#pragma unroll
                    for (int g = 0; g < 5; g++) {
                        if (g < 4) {
#pragma unroll
                            for (int i = g * 16; i < g * 16 + 16; i += 4) {
                                s[i] = fmaf(s[i], kScale, -m0);
                                s[i + 1] = fmaf(s[i + 1], kScale, -m0);
                                s[i + 2] = fmaf(s[i + 2], kScale, -m1);
                                s[i + 3] = fmaf(s[i + 3], kScale, -m1);
                            }
                        }
                        if (g > 0) {
#pragma unroll
                            for (int i = g * 16 - 16; i < g * 16; i += 4) {
                                c0 = __vimax3_s32(c0, __float_as_int(s[i]), __float_as_int(s[i + 1]));
                                c1 = __vimax3_s32(c1, __float_as_int(s[i + 2]), __float_as_int(s[i + 3]));
                            }
#pragma unroll
                            for (int i = (g - 1) * SPEC / 4; i < g * SPEC / 4; i++) e[i] = ex2(s[i]);
                        }
                        if (g > 0 && g < 4) {
                            reg_fence(s);
                            asm volatile("" : "+r"(c0), "+r"(c1)::"memory");
#pragma unroll
                            for (int i = (g - 1) * SPEC / 4; i < g * SPEC / 4; i++) asm volatile("" : "+f"(e[i])::"memory");
                            breathe();
                            reg_fence(s);
                        }
                    }
                    if (__any_sync(0xffffffffu, max(c0, c1) > 0x41000000)) {
                        float d0, d1;
                        rowmax(d0, d1);
                        d0 = fmaxf(d0, 0.f);
                        d1 = fmaxf(d1, 0.f);
                        const float a0 = ex2(-d0), a1 = ex2(-d1);
                        m0 += d0; m1 += d1; l0 *= a0; l1 *= a1;
#pragma unroll
                        for (int i = 0; i < 64; i += 4) {
                            s[i] -= d0; s[i + 1] -= d0; s[i + 2] -= d1; s[i + 3] -= d1;
                        }
#pragma unroll
                        for (int i = 0; i < SPEC; i++) e[i] = ex2(s[i]);
#pragma unroll
                        for (int i = 0; i < 128; i += 4) {
                            o[i] *= a0; o[i + 1] *= a0; o[i + 2] *= a1; o[i + 3] *= a1;
                        }
                    }
                }
                TSR(0);
                auto expchunk = [&](int c) {
#pragma unroll
                    for (int i = c * 16; i < c * 16 + 16; i += 4) {
                        const float e0 = i < SPEC ? e[i < SPEC ? i : 0] : ex2(s[i]);
                        const float e1 = i < SPEC ? e[i < SPEC ? i + 1 : 0] : ex2(s[i + 1]);
                        const float e2 = i < SPEC ? e[i < SPEC ? i + 2 : 0] : ex2(s[i + 2]);
                        const float e3 = i < SPEC ? e[i < SPEC ? i + 3 : 0] : ex2(s[i + 3]);
                        l0 += e0 + e1;
                        l1 += e2 + e3;
                        p[i / 2] = pack_bf16(e0, e1);
                        p[i / 2 + 1] = pack_bf16(e2, e3);
                    }
                };
#pragma unroll
                for (int c = 0; c < PRE_CHUNKS; c++) expchunk(c);

#pragma unroll
                for (int c = 0; c < 4; c++) {
                    mbar_wait(BAR(kBarVFull + c), par);
                    if (c == 0) TSR(4);
                    wgmma_fence();
#pragma unroll
                    for (int k = 0; k < 2; k++) {
                        const int kk = c * 2 + k;
                        wgmma_pv(o, p[kk * 4], p[kk * 4 + 1], p[kk * 4 + 2], p[kk * 4 + 3],
                                 descV + (c * kChunk + k * 2048) / 16, (j | kk) != 0);
                    }
                    wgmma_commit();
                    if (c + 1 >= PRE_CHUNKS && c + 1 < 4) expchunk(c + 1);
                }
                if (TURN2 && wg == 1) bar_arrive(1, 256);
                TSR(5);
                wgmma_wait<3>();
                if (lane == 0) mbar_arrive(BAR(kBarVEmpty + 0));
                wgmma_wait<2>();
                if (lane == 0) mbar_arrive(BAR(kBarVEmpty + 1));
                wgmma_wait<1>();
                if (lane == 0) mbar_arrive(BAR(kBarVEmpty + 2));
                wgmma_wait<0>();
                if (lane == 0) mbar_arrive(BAR(kBarVEmpty + 3));
                reg_fence(o);
                reg_fence(p);
                TSR(6);
                if (j == 0 && r > 0) {
                    asm volatile("cp.async.bulk.wait_group.read 0;" ::: "memory");
                    if (lane == 0) mbar_arrive(BAR(kBarXFree));
                }
                TSFLUSH(it);
                TSG(100 + it);
            }

            l0 += __shfl_xor_sync(0xffffffffu, l0, 1);
            l1 += __shfl_xor_sync(0xffffffffu, l1, 1);
            l0 += __shfl_xor_sync(0xffffffffu, l0, 2);
            l1 += __shfl_xor_sync(0xffffffffu, l1, 2);
            const float i0 = __fdividef(1.f, l0);
            i1 = __fdividef(1.f, l1);
            if (r + 1 < nrounds) {
                mbar_wait(BAR(kBarQEmpty + 1), r & 1);
                TS(112 + r * 2);
                stage_o(XBUF(r, 1) + warp * 4096, r, 0, i0);
                TS(113 + r * 2);
            } else {
                const uint32_t slot = XBUF(r, wg) + (warp & 3) * 8192;
                stage_o(slot, r, 0, i0);
                stage_o(slot + 4096, r, 1, i1);
                asm volatile("cp.async.bulk.wait_group 0;" ::: "memory");
            }
        }
        TS(125);
        TSG(127);
        if (TURN2 && wg == 0) bar_sync(1, 256);
    }
}

typedef CUresult (*EncodeFn)(CUtensorMap*, CUtensorMapDataType, cuuint32_t, void*, const cuuint64_t*, const cuuint64_t*,
                             const cuuint32_t*, const cuuint32_t*, CUtensorMapInterleave, CUtensorMapSwizzle,
                             CUtensorMapL2promotion, CUtensorMapFloatOOBfill);

void make_map(EncodeFn fn, CUtensorMap* m, const void* ptr, uint64_t rows, uint32_t box_rows, uint32_t nblk) {
    cuuint64_t dims[3] = {64, rows, 4};
    cuuint64_t strides[2] = {kD * 2, 128};
    cuuint32_t box[3] = {64, box_rows, nblk};
    cuuint32_t estr[3] = {1, 1, 1};
    fn(m, CU_TENSOR_MAP_DATA_TYPE_BFLOAT16, 3, const_cast<void*>(ptr), dims, strides, box, estr,
       CU_TENSOR_MAP_INTERLEAVE_NONE, CU_TENSOR_MAP_SWIZZLE_128B, CU_TENSOR_MAP_L2_PROMOTION_L2_128B,
       CU_TENSOR_MAP_FLOAT_OOB_FILL_NONE);
}

void make_map8(EncodeFn fn, CUtensorMap* m, const void* ptr, uint64_t rows) {
    cuuint64_t dims[4] = {64, 8, 4, rows / 8};
    cuuint64_t strides[3] = {kD * 2, 128, kD * 16};
    cuuint32_t box[4] = {64, 8, 4, 8};
    cuuint32_t estr[4] = {1, 1, 1, 1};
    fn(m, CU_TENSOR_MAP_DATA_TYPE_BFLOAT16, 4, const_cast<void*>(ptr), dims, strides, box, estr,
       CU_TENSOR_MAP_INTERLEAVE_NONE, CU_TENSOR_MAP_SWIZZLE_128B, CU_TENSOR_MAP_L2_PROMOTION_L2_128B,
       CU_TENSOR_MAP_FLOAT_OOB_FILL_NONE);
}

}

extern "C" void kernel_launch(void* const* d_in, const int* in_sizes, int n_in, void* d_out, int out_size) {
    (void)in_sizes; (void)n_in; (void)out_size;
    static EncodeFn encode = nullptr;
    if (!encode) {
        void* fn = nullptr;
        cudaDriverEntryPointQueryResult st;
        cudaGetDriverEntryPoint("cuTensorMapEncodeTiled", &fn, cudaEnableDefault, &st);
        encode = (EncodeFn)fn;
        cudaFuncSetAttribute(gqa_attn_kernel, cudaFuncAttributeMaxDynamicSharedMemorySize, kSmemBytes);
    }
    CUtensorMap tmQ, tmK, tmV, tmO, tmQ8;
    make_map8(encode, &tmQ8, d_in[0], (uint64_t)kHeads * kRowsPerHead);
    make_map(encode, &tmQ, d_in[0], (uint64_t)kHeads * kRowsPerHead, 8, 4);
    make_map(encode, &tmK, d_in[1], (uint64_t)kHeads * kSk, 128, 1);
    make_map(encode, &tmV, d_in[2], (uint64_t)kHeads * kSk, 32, 4);
    make_map(encode, &tmO, d_out, (uint64_t)kHeads * kRowsPerHead, 8, 4);
    gqa_attn_kernel<<<kGrid, kThreads, kSmemBytes>>>(tmQ, tmK, tmV, tmO, tmQ8);
}
```

```cpp
#include <cuda.h>
#include <cuda_bf16.h>
#include <cuda_runtime.h>
#include <stdint.h>

#define PRE_CHUNKS 2
#define PRE_FIRST 1
#define SPEC 16
#define LATE 6500
#define LATE2 14500
#define PROL 2
#define OSPLIT 3
#define QSLOTS0 0x00005555u
#define QSLOTS1 0x000FF000u
#define PSLOTS0 0x55000000u
#define PSLOTS1 0x55555550u
#define TMPF 1
#define QWAIT_EARLY 1
#define HOT 0
#define MONITOR 0

namespace {

constexpr int kD = 256;
constexpr int kSk = 512;
constexpr int kRowsPerHead = 384;
constexpr int kHeads = 128;
constexpr int kTriples = 44;
constexpr int kGrid = 3 * kTriples;
constexpr int kThreads = 384;
constexpr int kTilesKV = 4;

constexpr int kChunk = 16384;
constexpr int kOffK = 0;
constexpr int kOffV = 65536;
constexpr int kOffX = 131072;
constexpr int kOffBar = 229376;
constexpr int kSmemBytes = kOffBar + 256;

constexpr int kBarKFull = 0, kBarKEmpty = 4, kBarVFull = 8, kBarVEmpty = 12;
constexpr int kBarQFull = 16, kBarQEmpty = 18, kBarOFull = 20, kBarOEmpty = 22;

__device__ __forceinline__ uint32_t smem_u32(const void* p) { return (uint32_t)__cvta_generic_to_shared(p); }

__device__ __forceinline__ void mbar_init(uint32_t bar, uint32_t cnt) {
    asm volatile("mbarrier.init.shared::cta.b64 [%0], %1;" ::"r"(bar), "r"(cnt) : "memory");
}
__device__ __forceinline__ void mbar_expect_tx(uint32_t bar, uint32_t bytes) {
    asm volatile("mbarrier.arrive.expect_tx.shared::cta.b64 _, [%0], %1;" ::"r"(bar), "r"(bytes) : "memory");
}
__device__ __forceinline__ void mbar_arrive(uint32_t bar) {
    asm volatile("mbarrier.arrive.shared::cta.b64 _, [%0];" ::"r"(bar) : "memory");
}
__device__ __forceinline__ void mbar_wait(uint32_t bar, uint32_t parity) {
    asm volatile(
        "{\n"
        ".reg .pred p;\n"
        ".reg .u32 n;\n"
        "mbarrier.try_wait.parity.shared::cta.b64 p, [%0], %1;\n"
        "@p bra DONE_%=;\n"
        "mov.u32 n, 0;\n"
        "LOOP_%=:\n"
        "mbarrier.try_wait.parity.shared::cta.b64 p, [%0], %1;\n"
        "@p bra DONE_%=;\n"
        "add.u32 n, n, 1;\n"
        "setp.lt.u32 p, n, 0x400000;\n"
        "@p bra LOOP_%=;\n"
        "trap;\n"
        "DONE_%=:\n"
        "}\n" ::"r"(bar), "r"(parity) : "memory");
}
__device__ __forceinline__ void tma_load3(uint32_t dst, const CUtensorMap* map, uint32_t bar, int c0, int c1, int c2, uint64_t pol) {
    asm volatile(
        "cp.async.bulk.tensor.3d.shared::cluster.global.mbarrier::complete_tx::bytes.L2::cache_hint [%0], [%1, {%3, %4, %5}], [%2], %6;"
        ::"r"(dst), "l"(map), "r"(bar), "r"(c0), "r"(c1), "r"(c2), "l"(pol) : "memory");
}
__device__ __forceinline__ void tma_store3(const CUtensorMap* map, uint32_t src, int c0, int c1, int c2) {
    asm volatile("cp.async.bulk.tensor.3d.global.shared::cta.bulk_group [%0, {%2, %3, %4}], [%1];"
                 ::"l"(map), "r"(src), "r"(c0), "r"(c1), "r"(c2) : "memory");
}
__device__ __forceinline__ void bar_sync(int id, int n) { asm volatile("bar.sync %0, %1;" ::"r"(id), "r"(n) : "memory"); }
__device__ __forceinline__ void bar_arrive(int id, int n) { asm volatile("bar.arrive %0, %1;" ::"r"(id), "r"(n) : "memory"); }

__device__ __forceinline__ void wgmma_fence() { asm volatile("wgmma.fence.sync.aligned;" ::: "memory"); }
__device__ __forceinline__ void wgmma_commit() { asm volatile("wgmma.commit_group.sync.aligned;" ::: "memory"); }
template <int N> __device__ __forceinline__ void wgmma_wait() { asm volatile("wgmma.wait_group.sync.aligned %0;" ::"n"(N) : "memory"); }

template <int N> __device__ __forceinline__ void reg_fence(float (&r)[N]) {
#pragma unroll
    for (int i = 0; i < N; i++) asm volatile("" : "+f"(r[i])::"memory");
}
template <int N> __device__ __forceinline__ void reg_fence(uint32_t (&r)[N]) {
#pragma unroll
    for (int i = 0; i < N; i++) asm volatile("" : "+r"(r[i])::"memory");
}

__device__ __forceinline__ uint64_t make_desc(uint32_t addr, uint32_t lbo, uint32_t sbo) {
    return (uint64_t)((addr & 0x3FFFF) >> 4) | ((uint64_t)(lbo >> 4) << 16) | ((uint64_t)(sbo >> 4) << 32) | (1ull << 62);
}

#define F8(a, i) "+f"(a[i]), "+f"(a[i + 1]), "+f"(a[i + 2]), "+f"(a[i + 3]), "+f"(a[i + 4]), "+f"(a[i + 5]), "+f"(a[i + 6]), "+f"(a[i + 7])
#define F32(a, i) F8(a, i), F8(a, i + 8), F8(a, i + 16), F8(a, i + 24)

__device__ __forceinline__ void wgmma_qk(float (&d)[64], uint64_t da, uint64_t db, int scale_d) {
    asm volatile(
        "{\n.reg .pred p;\nsetp.ne.b32 p, %66, 0;\n"
        "wgmma.mma_async.sync.aligned.m64n128k16.f32.bf16.bf16 "
        "{%0, %1, %2, %3, %4, %5, %6, %7, %8, %9, %10, %11, %12, %13, %14, %15, "
        "%16, %17, %18, %19, %20, %21, %22, %23, %24, %25, %26, %27, %28, %29, %30, %31, "
        "%32, %33, %34, %35, %36, %37, %38, %39, %40, %41, %42, %43, %44, %45, %46, %47, "
        "%48, %49, %50, %51, %52, %53, %54, %55, %56, %57, %58, %59, %60, %61, %62, %63}, "
        "%64, %65, p, 1, 1, 0, 0;\n}\n"
        : F32(d, 0), F32(d, 32)
        : "l"(da), "l"(db), "r"(scale_d));
}
__device__ __forceinline__ void wgmma_pv(float (&d)[128], uint32_t a0, uint32_t a1, uint32_t a2, uint32_t a3, uint64_t db, int scale_d) {
    asm volatile(
        "{\n.reg .pred p;\nsetp.ne.b32 p, %133, 0;\n"
        "wgmma.mma_async.sync.aligned.m64n256k16.f32.bf16.bf16 "
        "{%0, %1, %2, %3, %4, %5, %6, %7, %8, %9, %10, %11, %12, %13, %14, %15, "
        "%16, %17, %18, %19, %20, %21, %22, %23, %24, %25, %26, %27, %28, %29, %30, %31, "
        "%32, %33, %34, %35, %36, %37, %38, %39, %40, %41, %42, %43, %44, %45, %46, %47, "
        "%48, %49, %50, %51, %52, %53, %54, %55, %56, %57, %58, %59, %60, %61, %62, %63, "
        "%64, %65, %66, %67, %68, %69, %70, %71, %72, %73, %74, %75, %76, %77, %78, %79, "
        "%80, %81, %82, %83, %84, %85, %86, %87, %88, %89, %90, %91, %92, %93, %94, %95, "
        "%96, %97, %98, %99, %100, %101, %102, %103, %104, %105, %106, %107, %108, %109, %110, %111, "
        "%112, %113, %114, %115, %116, %117, %118, %119, %120, %121, %122, %123, %124, %125, %126, %127}, "
        "{%128, %129, %130, %131}, %132, p, 1, 1, 1;\n}\n"
        : F32(d, 0), F32(d, 32), F32(d, 64), F32(d, 96)
        : "r"(a0), "r"(a1), "r"(a2), "r"(a3), "l"(db), "r"(scale_d));
}

__device__ __forceinline__ void breathe() { asm volatile("pmevent 0;" ::: "memory"); }
template <int N> __device__ __forceinline__ void pin(float* r) {
#pragma unroll
    for (int i = 0; i < N; i++) asm volatile("" : "+f"(r[i])::"memory");
}

__device__ __forceinline__ float ex2(float x) {
    float y;
    asm("ex2.approx.ftz.f32 %0, %1;" : "=f"(y) : "f"(x));
    return y;
}
__device__ __forceinline__ uint32_t pack_bf16(float lo, float hi) {
    uint32_t r;
    asm("cvt.rn.bf16x2.f32 %0, %1, %2;" : "=r"(r) : "f"(hi), "f"(lo));
    return r;
}

__device__ __forceinline__ bool elect_one() {
    uint32_t p;
    asm volatile("{\n.reg .pred P;\nelect.sync _|P, 0xffffffff;\nselp.u32 %0, 1, 0, P;\n}" : "=r"(p));
    return p;
}

template <bool B> struct Flag { static constexpr bool value = B; };

__device__ __forceinline__ uint32_t clock32() {
    uint32_t c;
    asm volatile("mov.u32 %0, %%clock;" : "=r"(c));
    return c;
}
__device__ __forceinline__ void spin(uint32_t cycles) {
    const uint32_t t0 = clock32();
    while (clock32() - t0 < cycles) __nanosleep(32);
}

__global__ void __launch_bounds__(kThreads, 1)
gqa_attn_kernel(const __grid_constant__ CUtensorMap tmK, const __grid_constant__ CUtensorMap tmV,
                const __grid_constant__ CUtensorMap tmQ64, const __grid_constant__ CUtensorMap tmQ8,
                const __grid_constant__ CUtensorMap tmO, const uint8_t* __restrict__ qptr) {
    extern __shared__ __align__(1024) uint8_t smem[];
    if (threadIdx.x == 0) {
        asm volatile("prefetch.tensormap [%0];" ::"l"(&tmK) : "memory");
        asm volatile("prefetch.tensormap [%0];" ::"l"(&tmQ64) : "memory");
    }
    const uint32_t sbase = smem_u32(smem);
    const uint32_t bars = sbase + kOffBar;
    auto BAR = [&](int i) { return bars + 8u * i; };

    const int warp = __shfl_sync(0xffffffffu, threadIdx.x >> 5, 0);
    const int lane = threadIdx.x & 31;
    const int triple = blockIdx.x / 3;
    const int sub = blockIdx.x - 3 * triple;
    const int head0 = kTriples - 1 - triple;
    const int nrounds = (head0 + 2 * kTriples < kHeads) ? 3 : 2;
    auto ROW = [&](int r) { return (head0 + r * kTriples) * kRowsPerHead + sub * 128; };
    auto XBUF = [&](int r, int k) { return sbase + kOffX + ((3 - r + k) % 3) * 32768u; };

    uint64_t pol;
    asm volatile("createpolicy.fractional.L2::evict_first.b64 %0, 1.0;" : "=l"(pol));
    auto load_kv = [&](int r, int j, int c) {
        const int krow = (HOT ? 0 : head0 + r * kTriples) * kSk + j * 128 + (c < 4 ? 0 : (c - 4) * 32);
        const uint32_t f = BAR(kBarKFull + c + (c & 4));
        mbar_expect_tx(f, kChunk);
        tma_load3(sbase + c * kChunk, c < 4 ? &tmK : &tmV, f, 0, krow, c < 4 ? c : 0, pol);
    };
    auto load_q = [&](int r, int w) {
        mbar_expect_tx(BAR(kBarQFull + w), 32768);
        asm volatile(
            "cp.async.bulk.tensor.4d.shared::cluster.global.mbarrier::complete_tx::bytes.L2::cache_hint [%0], [%1, {%3, %3, %3, %4}], [%2], %5;"
            ::"r"(XBUF(r, w)), "l"(&tmQ64), "r"(BAR(kBarQFull + w)), "r"(0), "r"(((HOT ? 0 : ROW(r)) + w * 64) / 8), "l"(pol) : "memory");
    };

    if (warp == 8 && elect_one()) {
#pragma unroll
        for (int i = 0; i < 4; i++) {
            mbar_init(BAR(kBarKFull + i), 1);
            mbar_init(BAR(kBarKEmpty + i), 8);
            mbar_init(BAR(kBarVFull + i), 1);
            mbar_init(BAR(kBarVEmpty + i), 8);
        }
#pragma unroll
        for (int i = 0; i < 2; i++) {
            mbar_init(BAR(kBarQFull + i), 1);
            mbar_init(BAR(kBarQEmpty + i), 4);
            mbar_init(BAR(kBarOFull + i), 4);
            mbar_init(BAR(kBarOEmpty + i), 1);
        }
        asm volatile("fence.mbarrier_init.release.cluster;" ::: "memory");
        if (nrounds == 2) spin(LATE);
        load_kv(0, 0, 0);
        load_q(0, 0);
        load_kv(0, 0, 1);
        load_kv(0, 0, 2);
        load_kv(0, 0, 3);
        load_q(0, 1);
    }
    __syncthreads();

    if (warp >= 8) {
        asm volatile("setmaxnreg.dec.sync.aligned.u32 24;");
        if (warp == 8 && elect_one()) {
            if (TMPF >= 1) {
                asm volatile("prefetch.tensormap [%0];" ::"l"(&tmV) : "memory");
                asm volatile("prefetch.tensormap [%0];" ::"l"(&tmQ8) : "memory");
                asm volatile("prefetch.tensormap [%0];" ::"l"(&tmO) : "memory");
            }
            int it = 0, qrow = 0;
            uint32_t qslots = 0, qdst = 0;
#pragma unroll 1
            for (int r = 0; r < nrounds; r++) {
                if (nrounds == 2 && r == 1) spin(LATE2);
                const uint32_t spare = XBUF(r, 2);
                const int orow = ROW(r - 1);
                auto store_o = [&](int half, int g0, int g1) {
#pragma unroll
                    for (int g = g0; g < g1; g++) tma_store3(&tmO, spare + g * 4096, 0, orow + g * 16 + half * 8, 0);
                    asm volatile("cp.async.bulk.commit_group;" ::: "memory");
                };
                uint32_t pslots = HOT || r + 1 == nrounds ? 0u : r == 0 ? PSLOTS0 : PSLOTS1;
                const uint8_t* pq = qptr + (size_t)(ROW(r + 1) + (r == 0 ? 64 : 0)) * (kD * 2);
                if (r > 0) {
                    mbar_wait(BAR(kBarQEmpty), (r & 1) ^ 1);
                    load_q(r, 1);
                }
#pragma unroll 1
                for (int j = 0; j < kTilesKV; j++, it++, qslots >>= 8, pslots >>= 8) {
                    const uint32_t par = (it & 1) ^ 1;
                    if (j == 1 && r + 1 < nrounds) {
                        qslots = r == 0 ? QSLOTS0 : QSLOTS1;
                        qdst = spare;
                        qrow = HOT ? 0 : ROW(r + 1);
                    }
#pragma unroll
                    for (int c = 0; c < 8; c++) {
                        if (it == 0 && c < 4) continue;
                        if (it == 0 && c == 4) mbar_wait(BAR(kBarKFull + PROL), 0);
                        mbar_wait(BAR(kBarKEmpty + c + (c & 4)), par);
                        load_kv(r, j, c);
                        if (c == 0 && j == 1 && qslots) mbar_expect_tx(BAR(kBarQFull), 32768);
                        if ((qslots >> c) & 1) {
                            tma_load3(qdst, &tmQ8, BAR(kBarQFull), 0, qrow, 0, pol);
                            qdst += 4096;
                            qrow += 8;
                        }
                        if ((pslots >> c) & 1) {
                            asm volatile("cp.async.bulk.prefetch.L2.global [%0], 4096;" ::"l"(pq) : "memory");
                            pq += 4096;
                        }
                        if (c == 7 && r > 0 && j < 2) {
                            mbar_wait(BAR(kBarOFull), j);
                            store_o(j, 0, OSPLIT);
                        }
                        if (c == 3 && r > 0 && (j == 1 || j == 2)) {
                            store_o(j - 1, OSPLIT, 4);
                            mbar_wait(BAR(kBarOFull + 1), j - 1);
                            store_o(j - 1, 4, 8);
                            asm volatile("cp.async.bulk.wait_group.read 1;" ::: "memory");
                            if (j == 1) mbar_arrive(BAR(kBarOEmpty));
                            asm volatile("cp.async.bulk.wait_group.read 0;" ::: "memory");
                            if (j == 1) mbar_arrive(BAR(kBarOEmpty + 1));
                        }
                    }
                }
            }
        }
    } else {
        asm volatile("setmaxnreg.inc.sync.aligned.u32 240;");
        const int wg = warp >> 2;
        const float kScale = 0.0625f * 1.4426950408889634f;

        const uint64_t descK = make_desc(sbase + kOffK, 16, 1024);
        const uint64_t descV = make_desc(sbase + kOffV, 4096, 1024);

        float o[128];
        float s[64];
        uint32_t p[32];
        float m0, m1, l0, l1, i0 = 0.f, i1 = 0.f;
        uint32_t qpar = 0;

        auto pack4 = [&](int h, int k, uint32_t* t) {
            const float inv = h ? i1 : i0;
#pragma unroll
            for (int b = 0; b < 4; b++)
                t[b] = pack_bf16(o[16 * k + 4 * b + 2 * h] * inv, o[16 * k + 4 * b + 2 * h + 1] * inv);
            asm volatile("" : "+r"(t[0]), "+r"(t[1]), "+r"(t[2]), "+r"(t[3])::"memory");
        };
        auto stage = [&](uint32_t grp, int k, const uint32_t* t) {
            asm volatile("stmatrix.sync.aligned.m8n8.x4.shared.b16 [%0], {%1, %2, %3, %4};"
                         ::"r"(grp + (lane & 7) * 128 + (k >> 1) * 1024 + ((((k & 1) * 4 + (lane >> 3)) ^ (lane & 7)) << 4)),
                           "r"(t[0]), "r"(t[1]), "r"(t[2]), "r"(t[3]) : "memory");
        };
        auto hand_over = [&]() {
            asm volatile("fence.proxy.async.shared::cta;" ::: "memory");
            __syncwarp();
            if (lane == 0) mbar_arrive(BAR(kBarOFull + wg));
        };
        auto rowmax = [&](float& mx0, float& mx1) {
            mx0 = fmaxf(s[0], s[1]);
            mx1 = fmaxf(s[2], s[3]);
#pragma unroll
            for (int i = 4; i < 64; i += 4) {
                mx0 = fmaxf(mx0, fmaxf(s[i], s[i + 1]));
                mx1 = fmaxf(mx1, fmaxf(s[i + 2], s[i + 3]));
            }
            mx0 = fmaxf(mx0, __shfl_xor_sync(0xffffffffu, mx0, 1));
            mx1 = fmaxf(mx1, __shfl_xor_sync(0xffffffffu, mx1, 1));
            mx0 = fmaxf(mx0, __shfl_xor_sync(0xffffffffu, mx0, 2));
            mx1 = fmaxf(mx1, __shfl_xor_sync(0xffffffffu, mx1, 2));
        };
        auto shift = [&](int g) {
#pragma unroll
            for (int i = g * 16; i < g * 16 + 16; i += 4) {
                s[i] = fmaf(s[i], kScale, -m0);
                s[i + 1] = fmaf(s[i + 1], kScale, -m0);
                s[i + 2] = fmaf(s[i + 2], kScale, -m1);
                s[i + 3] = fmaf(s[i + 3], kScale, -m1);
            }
        };

        auto tile = [&](auto first, uint64_t descQ, uint32_t par, bool last) {
            constexpr bool kFirst = decltype(first)::value;
            constexpr int kPre = kFirst ? PRE_FIRST : PRE_CHUNKS;
            bar_sync(1 + wg, 256);
#pragma unroll
            for (int c = 0; c < 4; c++) {
                mbar_wait(BAR(kBarKFull + c), par);
                wgmma_fence();
#pragma unroll
                for (int k = 0; k < 4; k++)
                    wgmma_qk(s, descQ + (c * 1024 + k * 32) / 16, descK + (c * kChunk + k * 32) / 16, (c | k) != 0);
                wgmma_commit();
                if (c == 2) {
                    wgmma_wait<2>();
                    if (lane == 0) mbar_arrive(BAR(kBarKEmpty + 0));
                }
            }
            if (wg == 0) bar_arrive(2, 256);
            else if (kFirst) bar_arrive(3, 256);
            wgmma_wait<2>();
            if (lane == 0) mbar_arrive(BAR(kBarKEmpty + 1));
            wgmma_wait<1>();
            if (lane == 0) mbar_arrive(BAR(kBarKEmpty + 2));
            wgmma_wait<0>();
            if (lane == 0) mbar_arrive(BAR(kBarKEmpty + 3));
            if (lane == 0 && last) mbar_arrive(BAR(kBarQEmpty + wg));
            reg_fence(s);

            float e[SPEC];
            if (kFirst) {
                int c0 = max(__float_as_int(s[0]), __float_as_int(s[1]));
                int c1 = max(__float_as_int(s[2]), __float_as_int(s[3]));
#pragma unroll
                for (int i = 4; i < 64; i += 4) {
                    c0 = __vimax3_s32(c0, __float_as_int(s[i]), __float_as_int(s[i + 1]));
                    c1 = __vimax3_s32(c1, __float_as_int(s[i + 2]), __float_as_int(s[i + 3]));
                }
                c0 = max(c0, __shfl_xor_sync(0xffffffffu, c0, 1));
                c1 = max(c1, __shfl_xor_sync(0xffffffffu, c1, 1));
                c0 = max(c0, __shfl_xor_sync(0xffffffffu, c0, 2));
                c1 = max(c1, __shfl_xor_sync(0xffffffffu, c1, 2));
                float mx0 = __int_as_float(c0), mx1 = __int_as_float(c1);
                if (__any_sync(0xffffffffu, (c0 | c1) < 0)) rowmax(mx0, mx1);
                m0 = mx0 * kScale;
                m1 = mx1 * kScale;
                l0 = l1 = 0.f;
            } else {
                int c0 = 0, c1 = 0;
#pragma unroll
                for (int g = 0; g < 5; g++) {
                    if (g < 4) shift(g);
                    if (g > 0) {
#pragma unroll
                        for (int i = g * 16 - 16; i < g * 16; i += 4) {
                            c0 = __vimax3_s32(c0, __float_as_int(s[i]), __float_as_int(s[i + 1]));
                            c1 = __vimax3_s32(c1, __float_as_int(s[i + 2]), __float_as_int(s[i + 3]));
                        }
#pragma unroll
                        for (int i = (g - 1) * SPEC / 4; i < g * SPEC / 4; i++) e[i] = ex2(s[i]);
                    }
                    if (g > 0 && g < 4) {
                        reg_fence(s);
                        asm volatile("" : "+r"(c0), "+r"(c1)::"memory");
                        pin<SPEC / 4>(&e[(g - 1) * SPEC / 4]);
                        breathe();
                        reg_fence(s);
                    }
                }
                if (__any_sync(0xffffffffu, max(c0, c1) > 0x41000000)) {
                    float d0, d1;
                    rowmax(d0, d1);
                    d0 = fmaxf(d0, 0.f);
                    d1 = fmaxf(d1, 0.f);
                    const float a0 = ex2(-d0), a1 = ex2(-d1);
                    m0 += d0; m1 += d1; l0 *= a0; l1 *= a1;
#pragma unroll
                    for (int i = 0; i < 64; i += 4) {
                        s[i] -= d0; s[i + 1] -= d0; s[i + 2] -= d1; s[i + 3] -= d1;
                    }
#pragma unroll
                    for (int i = 0; i < SPEC; i++) e[i] = ex2(s[i]);
#pragma unroll
                    for (int i = 0; i < 128; i += 4) {
                        o[i] *= a0; o[i + 1] *= a0; o[i + 2] *= a1; o[i + 3] *= a1;
                    }
                }
            }
            auto expchunk = [&](int c) {
                if (kFirst) shift(c);
                constexpr int kSpec = kFirst ? 0 : SPEC;
#pragma unroll
                for (int i = c * 16; i < c * 16 + 16; i += 4) {
                    const float e0 = i < kSpec ? e[i < kSpec ? i : 0] : ex2(s[i]);
                    const float e1 = i < kSpec ? e[i < kSpec ? i + 1 : 0] : ex2(s[i + 1]);
                    const float e2 = i < kSpec ? e[i < kSpec ? i + 2 : 0] : ex2(s[i + 2]);
                    const float e3 = i < kSpec ? e[i < kSpec ? i + 3 : 0] : ex2(s[i + 3]);
                    l0 += e0 + e1;
                    l1 += e2 + e3;
                    p[i / 2] = pack_bf16(e0, e1);
                    p[i / 2 + 1] = pack_bf16(e2, e3);
                }
            };
#pragma unroll
            for (int c = 0; c < kPre; c++) expchunk(c);

#pragma unroll
            for (int c = 0; c < 4; c++) {
                mbar_wait(BAR(kBarVFull + c), par);
                if (c == 0 && kFirst && wg == 0) bar_sync(3, 256);
                wgmma_fence();
#pragma unroll
                for (int k = 0; k < 2; k++) {
                    const int kk = c * 2 + k;
                    wgmma_pv(o, p[kk * 4], p[kk * 4 + 1], p[kk * 4 + 2], p[kk * 4 + 3],
                             descV + (c * kChunk + k * 2048) / 16, !kFirst || kk != 0);
                }
                wgmma_commit();
                if (c + 1 >= kPre && c + 1 < 4) expchunk(c + 1);
            }
            if (wg == 1) bar_arrive(1, 256);
            if (last) {
                l0 += __shfl_xor_sync(0xffffffffu, l0, 1);
                l1 += __shfl_xor_sync(0xffffffffu, l1, 1);
                l0 += __shfl_xor_sync(0xffffffffu, l0, 2);
                l1 += __shfl_xor_sync(0xffffffffu, l1, 2);
                i0 = __fdividef(1.f, l0);
                i1 = __fdividef(1.f, l1);
                if (QWAIT_EARLY) mbar_wait(BAR(kBarQEmpty + 1), qpar);
            }
            wgmma_wait<3>();
            if (lane == 0) mbar_arrive(BAR(kBarVEmpty + 0));
            wgmma_wait<2>();
            if (lane == 0) mbar_arrive(BAR(kBarVEmpty + 1));
            wgmma_wait<1>();
            if (lane == 0) mbar_arrive(BAR(kBarVEmpty + 2));
            wgmma_wait<0>();
            if (lane == 0) mbar_arrive(BAR(kBarVEmpty + 3));
            reg_fence(o);
            reg_fence(p);
        };

        if (wg == 1) bar_arrive(1, 256);
        uint32_t parked[32];
#pragma unroll
        for (int i = 0; i < 32; i++) parked[i] = 0;
#pragma unroll 1
        for (int r = 0; r < nrounds; r++) {
            const uint64_t descQ = make_desc(XBUF(r, wg), 16, 4096);
            qpar = r & 1;
            mbar_wait(BAR(kBarQFull + wg), r & 1);
            tile(Flag<true>(), descQ, 0, false);
            if (r > 0) {
                mbar_wait(BAR(kBarOEmpty + wg), (r - 1) & 1);
#pragma unroll
                for (int k = 0; k < 8; k++) stage(XBUF(r, 2) + warp * 4096, k, &parked[4 * k]);
                hand_over();
            }
#pragma unroll 1
            for (int j = 1; j < kTilesKV; j++) tile(Flag<false>(), descQ, j & 1, j == kTilesKV - 1);

            if (r + 1 < nrounds) {
                if (!QWAIT_EARLY) mbar_wait(BAR(kBarQEmpty + 1), r & 1);
#pragma unroll
                for (int k = 0; k < 8; k++) {
                    uint32_t t[4];
                    pack4(0, k, t);
                    pack4(1, k, &parked[4 * k]);
                    breathe();
                    stage(XBUF(r, 1) + warp * 4096, k, t);
                    if (k < 7) pin<16>(&o[16 * k + 16]);
                }
                hand_over();
            } else {
                const uint32_t grp = XBUF(r, wg) + (warp & 3) * 8192;
#pragma unroll
                for (int h = 0; h < 2; h++) {
#pragma unroll
                    for (int k = 0; k < 8; k += 2) {
                        pack4(h, k, &parked[4 * k]);
                        pack4(h, k + 1, &parked[4 * k + 4]);
                        breathe();
                        stage(grp + h * 4096, k, &parked[4 * k]);
                        stage(grp + h * 4096, k + 1, &parked[4 * k + 4]);
                        if (k < 6) pin<32>(&o[16 * k + 32]);
                    }
                    asm volatile("fence.proxy.async.shared::cta;" ::: "memory");
                    __syncwarp();
                    if (elect_one()) tma_store3(&tmO, grp + h * 4096, 0, ROW(r) + warp * 16 + h * 8, 0);
                }
                asm volatile("cp.async.bulk.commit_group;" ::: "memory");
                asm volatile("cp.async.bulk.wait_group.read 0;" ::: "memory");
            }
        }
        if (wg == 0) bar_sync(1, 256);
    }
}

typedef CUresult (*EncodeFn)(CUtensorMap*, CUtensorMapDataType, cuuint32_t, void*, const cuuint64_t*, const cuuint64_t*,
                             const cuuint32_t*, const cuuint32_t*, CUtensorMapInterleave, CUtensorMapSwizzle,
                             CUtensorMapL2promotion, CUtensorMapFloatOOBfill);

void make_map(EncodeFn fn, CUtensorMap* m, const void* ptr, uint64_t rows, uint32_t box_rows, uint32_t nblk) {
    cuuint64_t dims[3] = {64, rows, 4};
    cuuint64_t strides[2] = {kD * 2, 128};
    cuuint32_t box[3] = {64, box_rows, nblk};
    cuuint32_t estr[3] = {1, 1, 1};
    fn(m, CU_TENSOR_MAP_DATA_TYPE_BFLOAT16, 3, const_cast<void*>(ptr), dims, strides, box, estr,
       CU_TENSOR_MAP_INTERLEAVE_NONE, CU_TENSOR_MAP_SWIZZLE_128B, CU_TENSOR_MAP_L2_PROMOTION_L2_128B,
       CU_TENSOR_MAP_FLOAT_OOB_FILL_NONE);
}

void make_map8(EncodeFn fn, CUtensorMap* m, const void* ptr, uint64_t rows) {
    cuuint64_t dims[4] = {64, 8, 4, rows / 8};
    cuuint64_t strides[3] = {kD * 2, 128, kD * 16};
    cuuint32_t box[4] = {64, 8, 4, 8};
    cuuint32_t estr[4] = {1, 1, 1, 1};
    fn(m, CU_TENSOR_MAP_DATA_TYPE_BFLOAT16, 4, const_cast<void*>(ptr), dims, strides, box, estr,
       CU_TENSOR_MAP_INTERLEAVE_NONE, CU_TENSOR_MAP_SWIZZLE_128B, CU_TENSOR_MAP_L2_PROMOTION_L2_128B,
       CU_TENSOR_MAP_FLOAT_OOB_FILL_NONE);
}

}

extern "C" void kernel_launch(void* const* d_in, const int* in_sizes, int n_in, void* d_out, int out_size) {
    (void)in_sizes; (void)n_in; (void)out_size;
    static EncodeFn encode = nullptr;
    if (!encode) {
        void* fn = nullptr;
        cudaDriverEntryPointQueryResult st;
        cudaGetDriverEntryPoint("cuTensorMapEncodeTiled", &fn, cudaEnableDefault, &st);
        encode = (EncodeFn)fn;
        cudaFuncSetAttribute(gqa_attn_kernel, cudaFuncAttributeMaxDynamicSharedMemorySize, kSmemBytes);
    }
    CUtensorMap tmK, tmV, tmQ64, tmQ8, tmO;
    make_map(encode, &tmK, d_in[1], (uint64_t)kHeads * kSk, 128, 1);
    make_map(encode, &tmV, d_in[2], (uint64_t)kHeads * kSk, 32, 4);
    make_map8(encode, &tmQ64, d_in[0], (uint64_t)kHeads * kRowsPerHead);
    make_map(encode, &tmQ8, d_in[0], (uint64_t)kHeads * kRowsPerHead, 8, 4);
    make_map(encode, &tmO, d_out, (uint64_t)kHeads * kRowsPerHead, 8, 4);
    gqa_attn_kernel<<<kGrid, kThreads, kSmemBytes>>>(tmK, tmV, tmQ64, tmQ8, tmO, (const uint8_t*)d_in[0]);
}
```

```cpp
#include <cuda.h>
#include <cuda_bf16.h>
#include <cuda_runtime.h>
#include <stdint.h>

#define INL __attribute__((always_inline))

namespace {

constexpr int kD = 256;
constexpr int kSk = 512;
constexpr int kRowsPerHead = 384;
constexpr int kHeads = 128;
constexpr int kTriples = 44;
constexpr int kGrid = 3 * kTriples;
constexpr int kThreads = 384;
constexpr int kTilesKV = 4;

constexpr int kPreMid = 2;
constexpr int kPreFirst = 1;
constexpr int kSpecExp = 16;
constexpr int kLate1 = 6500;
constexpr int kLate2 = 14500;
constexpr int kOSplit = 3;
constexpr uint32_t kQSlots0 = 0x00555500u, kQSlots1 = 0x0FF00000u;
constexpr uint32_t kPSlots0 = 0x55000000u, kPSlots1 = 0x55555550u;

constexpr int kChunk = 16384;
constexpr int kOffK = 0;
constexpr int kOffV = 65536;
constexpr int kOffX = 131072;
constexpr int kOffBar = 229376;
constexpr int kSmemBytes = kOffBar + 256;

constexpr int kBarKFull = 0, kBarKEmpty = 4, kBarVFull = 8, kBarVEmpty = 12;
constexpr int kBarQFull = 16, kBarOFull = 18, kBarOEmpty = 20, kBarQ0Empty = 22;

__device__ __forceinline__ uint32_t smem_u32(const void* p) { return (uint32_t)__cvta_generic_to_shared(p); }

__device__ __forceinline__ void mbar_init(uint32_t bar, uint32_t cnt) {
    asm volatile("mbarrier.init.shared::cta.b64 [%0], %1;" ::"r"(bar), "r"(cnt) : "memory");
}
__device__ __forceinline__ void mbar_expect_tx(uint32_t bar, uint32_t bytes) {
    asm volatile("mbarrier.arrive.expect_tx.shared::cta.b64 _, [%0], %1;" ::"r"(bar), "r"(bytes) : "memory");
}
__device__ __forceinline__ void mbar_arrive(uint32_t bar) {
    asm volatile("mbarrier.arrive.shared::cta.b64 _, [%0];" ::"r"(bar) : "memory");
}
__device__ __forceinline__ void mbar_arrive_if(bool p, uint32_t bar) {
    asm volatile("{\n.reg .pred q;\nsetp.ne.u32 q, %1, 0;\n@q mbarrier.arrive.shared::cta.b64 _, [%0];\n}" ::"r"(bar), "r"((uint32_t)p) : "memory");
}
__device__ __forceinline__ void mbar_wait(uint32_t bar, uint32_t parity) {
    asm volatile(
        "{\n"
        ".reg .pred p;\n"
        ".reg .u32 n;\n"
        "mbarrier.try_wait.parity.shared::cta.b64 p, [%0], %1;\n"
        "@p bra DONE_%=;\n"
        "mov.u32 n, 0;\n"
        "LOOP_%=:\n"
        "mbarrier.try_wait.parity.shared::cta.b64 p, [%0], %1;\n"
        "@p bra DONE_%=;\n"
        "add.u32 n, n, 1;\n"
        "setp.lt.u32 p, n, 0x400000;\n"
        "@p bra LOOP_%=;\n"
        "trap;\n"
        "DONE_%=:\n"
        "}\n" ::"r"(bar), "r"(parity) : "memory");
}
__device__ __forceinline__ void tma_load3(uint32_t dst, const CUtensorMap* map, uint32_t bar, int c0, int c1, int c2, uint64_t pol) {
    asm volatile(
        "cp.async.bulk.tensor.3d.shared::cluster.global.mbarrier::complete_tx::bytes.L2::cache_hint [%0], [%1, {%3, %4, %5}], [%2], %6;"
        ::"r"(dst), "l"(map), "r"(bar), "r"(c0), "r"(c1), "r"(c2), "l"(pol) : "memory");
}
__device__ __forceinline__ void tma_store3(const CUtensorMap* map, uint32_t src, int c0, int c1, int c2) {
    asm volatile("cp.async.bulk.tensor.3d.global.shared::cta.bulk_group [%0, {%2, %3, %4}], [%1];"
                 ::"l"(map), "r"(src), "r"(c0), "r"(c1), "r"(c2) : "memory");
}
__device__ __forceinline__ void bar_sync(int id, int n) { asm volatile("bar.sync %0, %1;" ::"r"(id), "r"(n) : "memory"); }
__device__ __forceinline__ void bar_arrive(int id, int n) { asm volatile("bar.arrive %0, %1;" ::"r"(id), "r"(n) : "memory"); }

__device__ __forceinline__ void wgmma_fence() { asm volatile("wgmma.fence.sync.aligned;" ::: "memory"); }
__device__ __forceinline__ void wgmma_commit() { asm volatile("wgmma.commit_group.sync.aligned;" ::: "memory"); }
template <int N> __device__ __forceinline__ void wgmma_wait() { asm volatile("wgmma.wait_group.sync.aligned %0;" ::"n"(N) : "memory"); }

template <int N> __device__ __forceinline__ void reg_fence(float (&r)[N]) {
#pragma unroll
    for (int i = 0; i < N; i++) asm volatile("" : "+f"(r[i])::"memory");
}
template <int N> __device__ __forceinline__ void reg_fence(uint32_t (&r)[N]) {
#pragma unroll
    for (int i = 0; i < N; i++) asm volatile("" : "+r"(r[i])::"memory");
}

__device__ __forceinline__ uint32_t desc_lo(uint32_t addr, uint32_t lbo) { return ((addr & 0x3FFFF) >> 4) | ((lbo >> 4) << 16); }
__host__ __device__ constexpr uint32_t desc_hi(uint32_t sbo) { return (sbo >> 4) | (1u << 30); }

template <int V> struct Int { static constexpr int value = V; };
template <int N, int I = 0, class F> __device__ __forceinline__ void static_for(F&& f) {
    if constexpr (I < N) {
        f(Int<I>());
        static_for<N, I + 1>(f);
    }
}

#define F8(a, i) "+f"(a[i]), "+f"(a[i + 1]), "+f"(a[i + 2]), "+f"(a[i + 3]), "+f"(a[i + 4]), "+f"(a[i + 5]), "+f"(a[i + 6]), "+f"(a[i + 7])
#define F32(a, i) F8(a, i), F8(a, i + 8), F8(a, i + 16), F8(a, i + 24)

template <int OFFA, int OFFB, int ACC>
__device__ __forceinline__ void wgmma_qk(float (&d)[64], uint32_t da, uint32_t db) {
    asm volatile(
        "{\n.reg .b32 lo;\n.reg .b64 a, b;\n"
        "add.u32 lo, %64, %66;\nmov.b64 a, {lo, %67};\nadd.u32 lo, %65, %68;\nmov.b64 b, {lo, %69};\n"
        "wgmma.mma_async.sync.aligned.m64n128k16.f32.bf16.bf16 "
        "{%0, %1, %2, %3, %4, %5, %6, %7, %8, %9, %10, %11, %12, %13, %14, %15, "
        "%16, %17, %18, %19, %20, %21, %22, %23, %24, %25, %26, %27, %28, %29, %30, %31, "
        "%32, %33, %34, %35, %36, %37, %38, %39, %40, %41, %42, %43, %44, %45, %46, %47, "
        "%48, %49, %50, %51, %52, %53, %54, %55, %56, %57, %58, %59, %60, %61, %62, %63}, "
        "a, b, %70, 1, 1, 0, 0;\n}\n"
        : F32(d, 0), F32(d, 32)
        : "r"(da), "r"(db), "n"(OFFA / 16), "n"(desc_hi(4096)), "n"(OFFB / 16), "n"(desc_hi(1024)), "n"(ACC));
}
template <int OFFB, int ACC>
__device__ __forceinline__ void wgmma_pv(float (&d)[128], const uint32_t* a, uint32_t db) {
    asm volatile(
        "{\n.reg .b32 lo;\n.reg .b64 b;\nadd.u32 lo, %132, %133;\nmov.b64 b, {lo, %134};\n"
        "wgmma.mma_async.sync.aligned.m64n256k16.f32.bf16.bf16 "
        "{%0, %1, %2, %3, %4, %5, %6, %7, %8, %9, %10, %11, %12, %13, %14, %15, "
        "%16, %17, %18, %19, %20, %21, %22, %23, %24, %25, %26, %27, %28, %29, %30, %31, "
        "%32, %33, %34, %35, %36, %37, %38, %39, %40, %41, %42, %43, %44, %45, %46, %47, "
        "%48, %49, %50, %51, %52, %53, %54, %55, %56, %57, %58, %59, %60, %61, %62, %63, "
        "%64, %65, %66, %67, %68, %69, %70, %71, %72, %73, %74, %75, %76, %77, %78, %79, "
        "%80, %81, %82, %83, %84, %85, %86, %87, %88, %89, %90, %91, %92, %93, %94, %95, "
        "%96, %97, %98, %99, %100, %101, %102, %103, %104, %105, %106, %107, %108, %109, %110, %111, "
        "%112, %113, %114, %115, %116, %117, %118, %119, %120, %121, %122, %123, %124, %125, %126, %127}, "
        "{%128, %129, %130, %131}, b, %135, 1, 1, 1;\n}\n"
        : F32(d, 0), F32(d, 32), F32(d, 64), F32(d, 96)
        : "r"(a[0]), "r"(a[1]), "r"(a[2]), "r"(a[3]), "r"(db), "n"(OFFB / 16), "n"(desc_hi(1024)), "n"(ACC));
}

__device__ __forceinline__ void breathe() { asm volatile("pmevent 0;" ::: "memory"); }
template <int N> __device__ __forceinline__ void pin(float* r) {
#pragma unroll
    for (int i = 0; i < N; i++) asm volatile("" : "+f"(r[i])::"memory");
}

__device__ __forceinline__ float ex2(float x) {
    float y;
    asm("ex2.approx.ftz.f32 %0, %1;" : "=f"(y) : "f"(x));
    return y;
}
__device__ __forceinline__ uint32_t pack_bf16(float lo, float hi) {
    uint32_t r;
    asm("cvt.rn.bf16x2.f32 %0, %1, %2;" : "=r"(r) : "f"(hi), "f"(lo));
    return r;
}

__device__ __forceinline__ bool elect_one() {
    uint32_t p;
    asm volatile("{\n.reg .pred P;\nelect.sync _|P, 0xffffffff;\nselp.u32 %0, 1, 0, P;\n}" : "=r"(p));
    return p;
}

enum { kModeFirst, kModeMid, kModeHold, kModeFlush };

__device__ __forceinline__ uint32_t clock32() {
    uint32_t c;
    asm volatile("mov.u32 %0, %%clock;" : "=r"(c));
    return c;
}
__device__ __forceinline__ void spin(uint32_t cycles) {
    const uint32_t t0 = clock32();
    while (clock32() - t0 < cycles) __nanosleep(32);
}

__global__ void __launch_bounds__(kThreads, 1)
gqa_attn_kernel(const __grid_constant__ CUtensorMap tmK, const __grid_constant__ CUtensorMap tmV,
                const __grid_constant__ CUtensorMap tmQ64, const __grid_constant__ CUtensorMap tmQ8,
                const __grid_constant__ CUtensorMap tmO, const uint8_t* __restrict__ qptr) {
    extern __shared__ __align__(1024) uint8_t smem[];
    if (threadIdx.x == 0) {
        asm volatile("prefetch.tensormap [%0];" ::"l"(&tmK) : "memory");
        asm volatile("prefetch.tensormap [%0];" ::"l"(&tmQ64) : "memory");
    }
    const uint32_t sbase = __shfl_sync(0xffffffffu, smem_u32(smem), 0);
    const uint32_t bars = sbase + kOffBar;
    auto BAR = [&](int i) INL { return bars + 8u * i; };

    const int warp = __shfl_sync(0xffffffffu, threadIdx.x >> 5, 0);
    const int lane = threadIdx.x & 31;
    const int triple = blockIdx.x / 3;
    const int sub = blockIdx.x - 3 * triple;
    const int head0 = kTriples - 1 - triple;
    const int nrounds = (head0 + 2 * kTriples < kHeads) ? 3 : 2;
    auto ROW = [&](int r) INL { return (head0 + r * kTriples) * kRowsPerHead + sub * 128; };
    auto XBUF = [&](int r, int k) INL { return sbase + kOffX + ((0x24924u >> (2 * (3 - r + k))) & 3) * 32768u; };

    uint64_t pol;
    asm volatile("createpolicy.fractional.L2::evict_first.b64 %0, 1.0;" : "=l"(pol));
    auto load_kv = [&](int r, int j, int c) INL {
        const int krow = (head0 + r * kTriples) * kSk + j * 128 + (c < 4 ? 0 : (c - 4) * 32);
        const uint32_t f = BAR(kBarKFull + c + (c & 4));
        mbar_expect_tx(f, kChunk);
        const uint32_t dst = c >= 6 && j == 3 && r + 1 == nrounds ? XBUF(r, 2) + (c - 6) * kChunk : sbase + c * kChunk;
        tma_load3(dst, c < 4 ? &tmK : &tmV, f, 0, krow, c < 4 ? c : 0, pol);
    };
    auto load_q = [&](int r, int w) INL {
        mbar_expect_tx(BAR(kBarQFull + w), 32768);
        asm volatile(
            "cp.async.bulk.tensor.4d.shared::cluster.global.mbarrier::complete_tx::bytes.L2::cache_hint [%0], [%1, {%3, %3, %3, %4}], [%2], %5;"
            ::"r"(XBUF(r, w)), "l"(&tmQ64), "r"(BAR(kBarQFull + w)), "r"(0), "r"((ROW(r) + w * 64) / 8), "l"(pol) : "memory");
    };

    if (warp == 8 && elect_one()) {
#pragma unroll
        for (int i = 0; i < 4; i++) {
            mbar_init(BAR(kBarKFull + i), 1);
            mbar_init(BAR(kBarKEmpty + i), 8);
            mbar_init(BAR(kBarVFull + i), 1);
            mbar_init(BAR(kBarVEmpty + i), 8);
        }
#pragma unroll
        for (int i = 0; i < 2; i++) {
            mbar_init(BAR(kBarQFull + i), 1);
            mbar_init(BAR(kBarOFull + i), 4);
            mbar_init(BAR(kBarOEmpty + i), 1);
        }
        mbar_init(BAR(kBarQ0Empty), 4);
        asm volatile("fence.mbarrier_init.release.cluster;" ::: "memory");
        if (nrounds == 2) spin(kLate1);
        load_kv(0, 0, 0);
        load_q(0, 0);
        load_kv(0, 0, 1);
        load_kv(0, 0, 2);
        load_kv(0, 0, 3);
        load_q(0, 1);
    }
    __syncthreads();

    if (warp >= 8) {
        asm volatile("setmaxnreg.dec.sync.aligned.u32 24;");
        if (warp == 8 && elect_one()) {
            asm volatile("prefetch.tensormap [%0];" ::"l"(&tmV) : "memory");
            asm volatile("prefetch.tensormap [%0];" ::"l"(&tmQ8) : "memory");
            asm volatile("prefetch.tensormap [%0];" ::"l"(&tmO) : "memory");
            int it = 0;
#pragma unroll 1
            for (int r = 0; r < nrounds; r++) {
                if (nrounds == 2 && r == 1) spin(kLate2);
                const uint32_t spare = XBUF(r, 2);
                const int orow = ROW(r - 1);
                auto store_o = [&](int half, int g0, int g1) INL {
#pragma unroll
                    for (int g = g0; g < g1; g++) tma_store3(&tmO, spare + g * 4096, 0, orow + g * 16 + half * 8, 0);
                    asm volatile("cp.async.bulk.commit_group;" ::: "memory");
                };
                uint32_t qslots = r + 1 == nrounds ? 0u : r == 0 ? kQSlots0 : kQSlots1;
                uint32_t pslots = r + 1 == nrounds ? 0u : r == 0 ? kPSlots0 : kPSlots1;
                uint32_t qdst = spare;
                int qrow = ROW(r + 1);
                const uint8_t* pq = qptr + (size_t)(ROW(r + 1) + (r == 0 ? 64 : 0)) * (kD * 2);
                if (r > 0) {
                    mbar_wait(BAR(kBarQ0Empty), (r & 1) ^ 1);
                    load_q(r, 1);
                }
#pragma unroll 1
                for (int j = 0; j < kTilesKV; j++, it++, qslots >>= 8, pslots >>= 8) {
                    const uint32_t par = (it & 1) ^ 1;
#pragma unroll
                    for (int c = 0; c < 8; c++) {
                        if (it == 0 && c < 4) continue;
                        if (it == 0 && c == 4) mbar_wait(BAR(kBarKFull + 2), 0);
                        mbar_wait(BAR(kBarKEmpty + c + (c & 4)), par);
                        load_kv(r, j, c);
                        if (c == 0 && j == 1 && qslots) mbar_expect_tx(BAR(kBarQFull), 32768);
                        if ((qslots >> c) & 1) {
                            tma_load3(qdst, &tmQ8, BAR(kBarQFull), 0, qrow, 0, pol);
                            qdst += 4096;
                            qrow += 8;
                        }
                        if ((pslots >> c) & 1) {
                            asm volatile("cp.async.bulk.prefetch.L2.global [%0], 4096;" ::"l"(pq) : "memory");
                            pq += 4096;
                        }
                        if (c == 7 && r > 0 && j < 2) {
                            mbar_wait(BAR(kBarOFull), j);
                            store_o(j, 0, kOSplit);
                        }
                        if (c == 3 && r > 0 && (j == 1 || j == 2)) {
                            store_o(j - 1, kOSplit, 4);
                            mbar_wait(BAR(kBarOFull + 1), j - 1);
                            store_o(j - 1, 4, 8);
                            asm volatile("cp.async.bulk.wait_group.read 1;" ::: "memory");
                            if (j == 1) mbar_arrive(BAR(kBarOEmpty));
                            asm volatile("cp.async.bulk.wait_group.read 0;" ::: "memory");
                            if (j == 1) mbar_arrive(BAR(kBarOEmpty + 1));
                        }
                    }
                }
            }
        }
    } else {
        asm volatile("setmaxnreg.inc.sync.aligned.u32 240;");
        const int wg = warp >> 2;
        const float kScale = 0.0625f * 1.4426950408889634f;

        const uint32_t descK = desc_lo(sbase + kOffK, 16);
        const uint32_t descV = desc_lo(sbase + kOffV, 4096);

        float o[128];
        float s[64];
        uint32_t p[32];
        float m0, m1, l0, l1, i0 = 0.f, i1 = 0.f;

        auto pack4 = [&](int h, int k, uint32_t* t) INL {
            const float inv = h ? i1 : i0;
#pragma unroll
            for (int b = 0; b < 4; b++)
                t[b] = pack_bf16(o[16 * k + 4 * b + 2 * h] * inv, o[16 * k + 4 * b + 2 * h + 1] * inv);
            asm volatile("" : "+r"(t[0]), "+r"(t[1]), "+r"(t[2]), "+r"(t[3])::"memory");
        };
        auto stage = [&](uint32_t grp, int k, const uint32_t* t) INL {
            asm volatile("stmatrix.sync.aligned.m8n8.x4.shared.b16 [%0], {%1, %2, %3, %4};"
                         ::"r"(grp + (lane & 7) * 128 + (k >> 1) * 1024 + ((((k & 1) * 4 + (lane >> 3)) ^ (lane & 7)) << 4)),
                           "r"(t[0]), "r"(t[1]), "r"(t[2]), "r"(t[3]) : "memory");
        };
        auto hand_over = [&]() INL {
            asm volatile("fence.proxy.async.shared::cta;" ::: "memory");
            __syncwarp();
            mbar_arrive_if(lane == 0, BAR(kBarOFull + wg));
        };
        auto rowmax = [&](float& mx0, float& mx1) INL {
            mx0 = fmaxf(s[0], s[1]);
            mx1 = fmaxf(s[2], s[3]);
#pragma unroll
            for (int i = 4; i < 64; i += 4) {
                mx0 = fmaxf(mx0, fmaxf(s[i], s[i + 1]));
                mx1 = fmaxf(mx1, fmaxf(s[i + 2], s[i + 3]));
            }
            mx0 = fmaxf(mx0, __shfl_xor_sync(0xffffffffu, mx0, 1));
            mx1 = fmaxf(mx1, __shfl_xor_sync(0xffffffffu, mx1, 1));
            mx0 = fmaxf(mx0, __shfl_xor_sync(0xffffffffu, mx0, 2));
            mx1 = fmaxf(mx1, __shfl_xor_sync(0xffffffffu, mx1, 2));
        };
        auto shift = [&](int g) INL {
#pragma unroll
            for (int i = g * 16; i < g * 16 + 16; i += 4) {
                s[i] = fmaf(s[i], kScale, -m0);
                s[i + 1] = fmaf(s[i + 1], kScale, -m0);
                s[i + 2] = fmaf(s[i + 2], kScale, -m1);
                s[i + 3] = fmaf(s[i + 3], kScale, -m1);
            }
        };

        uint32_t held[16];
        uint32_t parked[32];
        auto tile = [&](auto mode, uint32_t descQ, uint32_t descVhi, uint32_t par, bool last, bool flag) INL {
            constexpr bool kFirst = decltype(mode)::value == kModeFirst;
            constexpr bool kHold = decltype(mode)::value == kModeHold;
            constexpr bool kFlush = decltype(mode)::value == kModeFlush;
            constexpr int kPre = kFirst ? kPreFirst : kPreMid;
            constexpr int kSpec = kFirst || kFlush ? 0 : kSpecExp;
            bar_sync(1 + wg, 256);
            static_for<4>([&](auto ci) INL {
                constexpr int c = ci.value;
                mbar_wait(BAR(kBarKFull + c), par);
                wgmma_fence();
                static_for<4>([&](auto ki) INL {
                    constexpr int k = ki.value;
                    wgmma_qk<c * 1024 + k * 32, c * kChunk + k * 32, (c | k) != 0>(s, descQ, descK);
                });
                wgmma_commit();
                if (c == 0 && kFirst && flag) hand_over();
                if (c == 2) {
                    wgmma_wait<2>();
                    if (lane == 0) mbar_arrive(BAR(kBarKEmpty + 0));
                }
            });
            if (wg == 0) bar_arrive(2, 256);
            else if (kFirst) bar_arrive(3, 256);
            wgmma_wait<2>();
            if (lane == 0) mbar_arrive(BAR(kBarKEmpty + 1));
            wgmma_wait<1>();
            if (lane == 0) mbar_arrive(BAR(kBarKEmpty + 2));
            wgmma_wait<0>();
            if (lane == 0) mbar_arrive(BAR(kBarKEmpty + 3));
            if (lane == 0 && last && wg == 0) mbar_arrive(BAR(kBarQ0Empty));
            reg_fence(s);

            float e[kSpecExp];
            if (kFirst) {
                int c0 = max(__float_as_int(s[0]), __float_as_int(s[1]));
                int c1 = max(__float_as_int(s[2]), __float_as_int(s[3]));
#pragma unroll
                for (int i = 4; i < 64; i += 4) {
                    c0 = __vimax3_s32(c0, __float_as_int(s[i]), __float_as_int(s[i + 1]));
                    c1 = __vimax3_s32(c1, __float_as_int(s[i + 2]), __float_as_int(s[i + 3]));
                }
                c0 = max(c0, __shfl_xor_sync(0xffffffffu, c0, 1));
                c1 = max(c1, __shfl_xor_sync(0xffffffffu, c1, 1));
                c0 = max(c0, __shfl_xor_sync(0xffffffffu, c0, 2));
                c1 = max(c1, __shfl_xor_sync(0xffffffffu, c1, 2));
                float mx0 = __int_as_float(c0), mx1 = __int_as_float(c1);
                if (__any_sync(0xffffffffu, (c0 | c1) < 0)) rowmax(mx0, mx1);
                m0 = mx0 * kScale;
                m1 = mx1 * kScale;
                l0 = l1 = 0.f;
            } else {
                int c0 = 0, c1 = 0;
#pragma unroll
                for (int g = 0; g < 5; g++) {
                    if (g < 4) shift(g);
                    if (g > 0) {
#pragma unroll
                        for (int i = g * 16 - 16; i < g * 16; i += 4) {
                            c0 = __vimax3_s32(c0, __float_as_int(s[i]), __float_as_int(s[i + 1]));
                            c1 = __vimax3_s32(c1, __float_as_int(s[i + 2]), __float_as_int(s[i + 3]));
                        }
#pragma unroll
                        for (int i = (g - 1) * kSpec / 4; i < g * kSpec / 4; i++) e[i] = ex2(s[i]);
                    }
                    if (g > 0 && g < 4) {
                        reg_fence(s);
                        asm volatile("" : "+r"(c0), "+r"(c1)::"memory");
                        if (kSpec) pin<kSpecExp / 4>(&e[(g - 1) * kSpecExp / 4]);
                        breathe();
                        reg_fence(s);
                    }
                }
                if (__any_sync(0xffffffffu, max(c0, c1) > 0x41000000)) {
                    float d0, d1;
                    rowmax(d0, d1);
                    const float n0 = m0 + fmaxf(d0, 0.f), n1 = m1 + fmaxf(d1, 0.f);
                    d0 = n0 - m0;
                    d1 = n1 - m1;
                    const float a0 = ex2(-d0), a1 = ex2(-d1);
                    m0 = n0; m1 = n1; l0 *= a0; l1 *= a1;
#pragma unroll
                    for (int i = 0; i < 64; i += 4) {
                        s[i] -= d0; s[i + 1] -= d0; s[i + 2] -= d1; s[i + 3] -= d1;
                    }
#pragma unroll
                    for (int i = 0; i < kSpec; i++) e[i] = ex2(s[i]);
                    if (kFlush) {
#pragma unroll
                        for (int i = 0; i < 16; i++) {
                            const float a = (i & 1) ? a1 : a0;
                            held[i] = pack_bf16(__uint_as_float(held[i] << 16) * a, __uint_as_float(held[i] & 0xffff0000u) * a);
                        }
                    }
#pragma unroll
                    for (int i = 0; i < 128; i += 4) {
                        o[i] *= a0; o[i + 1] *= a0; o[i + 2] *= a1; o[i + 3] *= a1;
                    }
                }
            }
            auto expchunk = [&](int c) INL {
                if (kFirst) shift(c);
#pragma unroll
                for (int i = c * 16; i < c * 16 + 16; i += 4) {
                    const float e0 = i < kSpec ? e[i < kSpec ? i : 0] : ex2(s[i]);
                    const float e1 = i < kSpec ? e[i < kSpec ? i + 1 : 0] : ex2(s[i + 1]);
                    const float e2 = i < kSpec ? e[i < kSpec ? i + 2 : 0] : ex2(s[i + 2]);
                    const float e3 = i < kSpec ? e[i < kSpec ? i + 3 : 0] : ex2(s[i + 3]);
                    l0 += e0 + e1;
                    l1 += e2 + e3;
                    p[i / 2] = pack_bf16(e0, e1);
                    p[i / 2 + 1] = pack_bf16(e2, e3);
                }
            };
#pragma unroll
            for (int c = 0; c < kPre; c++) expchunk(c);

            if (kHold) {
                static_for<2>([&](auto ci) INL {
                    constexpr int c = ci.value;
                    mbar_wait(BAR(kBarVFull + c), par);
                    wgmma_fence();
                    wgmma_pv<c * kChunk, 1>(o, &p[c * 8], descV);
                    wgmma_pv<c * kChunk + 2048, 1>(o, &p[c * 8 + 4], descV);
                    wgmma_commit();
                });
                bar_arrive(1, 256);
#pragma unroll
                for (int c = 2; c < 4; c++) {
                    mbar_wait(BAR(kBarVFull + c), par);
                    if (lane == 0) mbar_arrive(BAR(kBarVEmpty + c));
                }
                expchunk(2);
                expchunk(3);
                wgmma_wait<1>();
                if (lane == 0) mbar_arrive(BAR(kBarVEmpty + 0));
                wgmma_wait<0>();
                if (lane == 0) mbar_arrive(BAR(kBarVEmpty + 1));
#pragma unroll
                for (int i = 0; i < 16; i++) held[i] = p[16 + i];
                reg_fence(held);
                reg_fence(o);
                return;
            }
            static_for<4>([&](auto ci) INL {
                constexpr int c = ci.value;
                mbar_wait(BAR(kBarVFull + c), par);
                if (c == 0 && kFirst && wg == 0) bar_sync(3, 256);
                if (c == 0 && kFlush) {
                    bar_sync(4, 256);
                    wgmma_fence();
                    static_for<4>([&](auto ki) INL {
                        constexpr int k = ki.value;
                        wgmma_pv<(2 + k / 2) * kChunk + (k & 1) * 2048, 1>(o, &held[4 * k], descV);
                    });
                    breathe();
                    reg_fence(s);
#pragma unroll
                    for (int x = kPre; x < 4; x++) expchunk(x);
                    reg_fence(p);
                    breathe();
                }
                wgmma_fence();
                wgmma_pv<c * kChunk, !kFirst || c != 0>(o, &p[c * 8], c < 2 ? descV : descVhi);
                wgmma_pv<c * kChunk + 2048, 1>(o, &p[c * 8 + 4], c < 2 ? descV : descVhi);
                wgmma_commit();
                if (!kFlush && c + 1 >= kPre && c + 1 < 4) expchunk(c + 1);
            });
            if (wg == 1) bar_arrive(1, 256);
            else if (last && flag) bar_arrive(4, 256);
            if (last) {
                l0 += __shfl_xor_sync(0xffffffffu, l0, 1);
                l1 += __shfl_xor_sync(0xffffffffu, l1, 1);
                l0 += __shfl_xor_sync(0xffffffffu, l0, 2);
                l1 += __shfl_xor_sync(0xffffffffu, l1, 2);
                i0 = __fdividef(1.f, l0);
                i1 = __fdividef(1.f, l1);
                mbar_wait(BAR(kBarKEmpty + 3), 1);
            }
            wgmma_wait<3>();
            if (lane == 0) mbar_arrive(BAR(kBarVEmpty + 0));
            wgmma_wait<2>();
            if (lane == 0) mbar_arrive(BAR(kBarVEmpty + 1));
            wgmma_wait<1>();
            if (lane == 0) mbar_arrive(BAR(kBarVEmpty + 2));
            wgmma_wait<0>();
            if (lane == 0) mbar_arrive(BAR(kBarVEmpty + 3));
            reg_fence(o);
            reg_fence(p);
        };

#pragma unroll
        for (int i = 0; i < 128; i++) o[i] = 0.f;
        if (wg == 1) bar_arrive(1, 256);
        const uint32_t descVend = desc_lo(XBUF(nrounds - 1, 2) - 2 * kChunk, 4096);
#pragma unroll 1
        for (int r = 0; r < nrounds; r++) {
            if (r > 0) {
#pragma unroll
                for (int k = 0; k < 8; k++) {
                    uint32_t t[4];
                    pack4(0, k, t);
                    pack4(1, k, &parked[4 * k]);
                    breathe();
                    stage(XBUF(r, 2) + warp * 4096, k, t);
                    if (k < 7) pin<16>(&o[16 * k + 16]);
                }
            } else {
                breathe();
#pragma unroll
                for (int i = 0; i < 32; i++) asm volatile("mov.u32 %0, 0;" : "=r"(parked[i]));
            }
            const uint32_t descQ = desc_lo(XBUF(r, wg), 16);
            mbar_wait(BAR(kBarQFull + wg), r & 1);
            tile(Int<kModeFirst>(), descQ, descV, 0, false, r > 0);
            if (r > 0) {
                mbar_wait(BAR(kBarOEmpty + wg), (r - 1) & 1);
#pragma unroll
                for (int k = 0; k < 8; k++) stage(XBUF(r, 2) + warp * 4096, k, &parked[4 * k]);
                hand_over();
            }
            const bool fin = r + 1 == nrounds;
            const int jend = fin && wg == 1 ? 2 : kTilesKV;
#pragma unroll 1
            for (int j = 1; j < jend; j++) {
                const bool last = j == kTilesKV - 1;
                tile(Int<kModeMid>(), descQ, last && fin ? descVend : descV, j & 1, last, fin);
            }
        }
        const int r = nrounds - 1;
        if (wg == 1) {
            tile(Int<kModeHold>(), desc_lo(XBUF(r, 1), 16), descV, 0, false, true);
            tile(Int<kModeFlush>(), desc_lo(XBUF(r, 1), 16), descVend, 1, true, true);
        }
        const uint32_t grp = sbase + kOffK + warp * 8192;
#pragma unroll
        for (int h = 0; h < 2; h++) {
#pragma unroll
            for (int k = 0; k < 8; k += 2) {
                uint32_t t[8];
                pack4(h, k, t);
                pack4(h, k + 1, t + 4);
                breathe();
                stage(grp + h * 4096, k, t);
                stage(grp + h * 4096, k + 1, t + 4);
                if (k < 6) pin<32>(&o[16 * k + 32]);
            }
            asm volatile("fence.proxy.async.shared::cta;" ::: "memory");
            __syncwarp();
            if (elect_one()) tma_store3(&tmO, grp + h * 4096, 0, ROW(r) + warp * 16 + h * 8, 0);
        }
        asm volatile("cp.async.bulk.commit_group;" ::: "memory");
        asm volatile("cp.async.bulk.wait_group.read 0;" ::: "memory");
        if (wg == 0) bar_sync(1, 256);
    }
}

typedef CUresult (*EncodeFn)(CUtensorMap*, CUtensorMapDataType, cuuint32_t, void*, const cuuint64_t*, const cuuint64_t*,
                             const cuuint32_t*, const cuuint32_t*, CUtensorMapInterleave, CUtensorMapSwizzle,
                             CUtensorMapL2promotion, CUtensorMapFloatOOBfill);

void make_map(EncodeFn fn, CUtensorMap* m, const void* ptr, uint64_t rows, uint32_t box_rows, uint32_t nblk) {
    cuuint64_t dims[3] = {64, rows, 4};
    cuuint64_t strides[2] = {kD * 2, 128};
    cuuint32_t box[3] = {64, box_rows, nblk};
    cuuint32_t estr[3] = {1, 1, 1};
    fn(m, CU_TENSOR_MAP_DATA_TYPE_BFLOAT16, 3, const_cast<void*>(ptr), dims, strides, box, estr,
       CU_TENSOR_MAP_INTERLEAVE_NONE, CU_TENSOR_MAP_SWIZZLE_128B, CU_TENSOR_MAP_L2_PROMOTION_L2_128B,
       CU_TENSOR_MAP_FLOAT_OOB_FILL_NONE);
}

void make_map8(EncodeFn fn, CUtensorMap* m, const void* ptr, uint64_t rows) {
    cuuint64_t dims[4] = {64, 8, 4, rows / 8};
    cuuint64_t strides[3] = {kD * 2, 128, kD * 16};
    cuuint32_t box[4] = {64, 8, 4, 8};
    cuuint32_t estr[4] = {1, 1, 1, 1};
    fn(m, CU_TENSOR_MAP_DATA_TYPE_BFLOAT16, 4, const_cast<void*>(ptr), dims, strides, box, estr,
       CU_TENSOR_MAP_INTERLEAVE_NONE, CU_TENSOR_MAP_SWIZZLE_128B, CU_TENSOR_MAP_L2_PROMOTION_L2_128B,
       CU_TENSOR_MAP_FLOAT_OOB_FILL_NONE);
}

}

extern "C" void kernel_launch(void* const* d_in, const int* in_sizes, int n_in, void* d_out, int out_size) {
    (void)in_sizes; (void)n_in; (void)out_size;
    static EncodeFn encode = nullptr;
    if (!encode) {
        void* fn = nullptr;
        cudaDriverEntryPointQueryResult st;
        cudaGetDriverEntryPoint("cuTensorMapEncodeTiled", &fn, cudaEnableDefault, &st);
        encode = (EncodeFn)fn;
        cudaFuncSetAttribute(gqa_attn_kernel, cudaFuncAttributeMaxDynamicSharedMemorySize, kSmemBytes);
    }
    CUtensorMap tmK, tmV, tmQ64, tmQ8, tmO;
    make_map(encode, &tmK, d_in[1], (uint64_t)kHeads * kSk, 128, 1);
    make_map(encode, &tmV, d_in[2], (uint64_t)kHeads * kSk, 32, 4);
    make_map8(encode, &tmQ64, d_in[0], (uint64_t)kHeads * kRowsPerHead);
    make_map(encode, &tmQ8, d_in[0], (uint64_t)kHeads * kRowsPerHead, 8, 4);
    make_map(encode, &tmO, d_out, (uint64_t)kHeads * kRowsPerHead, 8, 4);
    gqa_attn_kernel<<<kGrid, kThreads, kSmemBytes>>>(tmK, tmV, tmQ64, tmQ8, tmO, (const uint8_t*)d_in[0]);
}
```

```cpp
#include <cuda.h>
#include <cuda_bf16.h>
#include <cuda_runtime.h>
#include <stdint.h>

#define INL __attribute__((always_inline))
#pragma nv_diag_suppress 549

namespace {

constexpr int kD = 256;
constexpr int kSk = 512;
constexpr int kRowsPerHead = 384;
constexpr int kHeads = 128;
constexpr int kTriples = 44;
constexpr int kGrid = 3 * kTriples;
constexpr int kThreads = 384;
constexpr int kTilesKV = 4;

constexpr int kPreMid = 2;
constexpr int kPreFirst = 1;
constexpr int kSpecExp = 16;
constexpr int kFirstV = 5700;
constexpr int kFirstVGap = 300;
constexpr int kLate1 = 7500;
constexpr int kLate2 = 13500;
constexpr int kOSplit = 3;
constexpr uint32_t kQSlots0 = 0x00555500u, kQSlots1 = 0x0FF00000u;
constexpr uint32_t kPSlots0 = 0x55000000u, kPSlots1 = 0x55555550u;

constexpr int kChunk = 16384;
constexpr int kOffK = 0;
constexpr int kOffV = 65536;
constexpr int kOffX = 131072;
constexpr int kOffBar = 229376;
constexpr int kSmemBytes = kOffBar + 256;

constexpr int kBarKFull = 0, kBarKEmpty = 4, kBarVFull = 8, kBarVEmpty = 12;
constexpr int kBarQFull = 16, kBarOFull = 18, kBarOEmpty = 20, kBarQ0Empty = 22;

__device__ __forceinline__ uint32_t smem_u32(const void* p) { return (uint32_t)__cvta_generic_to_shared(p); }

__device__ __forceinline__ void mbar_init(uint32_t bar, uint32_t cnt) {
    asm volatile("mbarrier.init.shared::cta.b64 [%0], %1;" ::"r"(bar), "r"(cnt) : "memory");
}
__device__ __forceinline__ void mbar_expect_tx(uint32_t bar, uint32_t bytes) {
    asm volatile("mbarrier.arrive.expect_tx.shared::cta.b64 _, [%0], %1;" ::"r"(bar), "r"(bytes) : "memory");
}
__device__ __forceinline__ void mbar_arrive(uint32_t bar) {
    asm volatile("mbarrier.arrive.shared::cta.b64 _, [%0];" ::"r"(bar) : "memory");
}
__device__ __forceinline__ void mbar_arrive_if(bool p, uint32_t bar) {
    asm volatile("{\n.reg .pred q;\nsetp.ne.u32 q, %1, 0;\n@q mbarrier.arrive.shared::cta.b64 _, [%0];\n}" ::"r"(bar), "r"((uint32_t)p) : "memory");
}
__device__ __forceinline__ void mbar_wait(uint32_t bar, uint32_t parity) {
    asm volatile(
        "{\n"
        ".reg .pred p;\n"
        ".reg .u32 n;\n"
        "mbarrier.try_wait.parity.shared::cta.b64 p, [%0], %1;\n"
        "@p bra DONE_%=;\n"
        "mov.u32 n, 0;\n"
        "LOOP_%=:\n"
        "mbarrier.try_wait.parity.shared::cta.b64 p, [%0], %1;\n"
        "@p bra DONE_%=;\n"
        "add.u32 n, n, 1;\n"
        "setp.lt.u32 p, n, 0x400000;\n"
        "@p bra LOOP_%=;\n"
        "trap;\n"
        "DONE_%=:\n"
        "}\n" ::"r"(bar), "r"(parity) : "memory");
}
__device__ __forceinline__ void tma_load3(uint32_t dst, const CUtensorMap* map, uint32_t bar, int c0, int c1, int c2, uint64_t pol) {
    asm volatile(
        "cp.async.bulk.tensor.3d.shared::cluster.global.mbarrier::complete_tx::bytes.L2::cache_hint [%0], [%1, {%3, %4, %5}], [%2], %6;"
        ::"r"(dst), "l"(map), "r"(bar), "r"(c0), "r"(c1), "r"(c2), "l"(pol) : "memory");
}
__device__ __forceinline__ void tma_store3(const CUtensorMap* map, uint32_t src, int c0, int c1, int c2) {
    asm volatile("cp.async.bulk.tensor.3d.global.shared::cta.bulk_group [%0, {%2, %3, %4}], [%1];"
                 ::"l"(map), "r"(src), "r"(c0), "r"(c1), "r"(c2) : "memory");
}
__device__ __forceinline__ void bar_sync(int id, int n) { asm volatile("bar.sync %0, %1;" ::"r"(id), "r"(n) : "memory"); }
__device__ __forceinline__ void bar_arrive(int id, int n) { asm volatile("bar.arrive %0, %1;" ::"r"(id), "r"(n) : "memory"); }

__device__ __forceinline__ void wgmma_fence() { asm volatile("wgmma.fence.sync.aligned;" ::: "memory"); }
__device__ __forceinline__ void wgmma_commit() { asm volatile("wgmma.commit_group.sync.aligned;" ::: "memory"); }
template <int N> __device__ __forceinline__ void wgmma_wait() { asm volatile("wgmma.wait_group.sync.aligned %0;" ::"n"(N) : "memory"); }

template <int N> __device__ __forceinline__ void reg_fence(float (&r)[N]) {
#pragma unroll
    for (int i = 0; i < N; i++) asm volatile("" : "+f"(r[i])::"memory");
}
template <int N> __device__ __forceinline__ void reg_fence(uint32_t (&r)[N]) {
#pragma unroll
    for (int i = 0; i < N; i++) asm volatile("" : "+r"(r[i])::"memory");
}

__device__ __forceinline__ uint32_t desc_lo(uint32_t addr, uint32_t lbo) { return ((addr & 0x3FFFF) >> 4) | ((lbo >> 4) << 16); }
__host__ __device__ constexpr uint32_t desc_hi(uint32_t sbo) { return (sbo >> 4) | (1u << 30); }

template <int V> struct Int { static constexpr int value = V; };
template <int N, int I = 0, class F> __device__ __forceinline__ void static_for(F&& f) {
    if constexpr (I < N) {
        f(Int<I>());
        static_for<N, I + 1>(f);
    }
}

#define F8(a, i) "+f"(a[i]), "+f"(a[i + 1]), "+f"(a[i + 2]), "+f"(a[i + 3]), "+f"(a[i + 4]), "+f"(a[i + 5]), "+f"(a[i + 6]), "+f"(a[i + 7])
#define F32(a, i) F8(a, i), F8(a, i + 8), F8(a, i + 16), F8(a, i + 24)

template <int OFFA, int OFFB, int ACC>
__device__ __forceinline__ void wgmma_qk(float (&d)[64], uint32_t da, uint32_t db) {
    asm volatile(
        "{\n.reg .b32 lo;\n.reg .b64 a, b;\n"
        "add.u32 lo, %64, %66;\nmov.b64 a, {lo, %67};\nadd.u32 lo, %65, %68;\nmov.b64 b, {lo, %69};\n"
        "wgmma.mma_async.sync.aligned.m64n128k16.f32.bf16.bf16 "
        "{%0, %1, %2, %3, %4, %5, %6, %7, %8, %9, %10, %11, %12, %13, %14, %15, "
        "%16, %17, %18, %19, %20, %21, %22, %23, %24, %25, %26, %27, %28, %29, %30, %31, "
        "%32, %33, %34, %35, %36, %37, %38, %39, %40, %41, %42, %43, %44, %45, %46, %47, "
        "%48, %49, %50, %51, %52, %53, %54, %55, %56, %57, %58, %59, %60, %61, %62, %63}, "
        "a, b, %70, 1, 1, 0, 0;\n}\n"
        : F32(d, 0), F32(d, 32)
        : "r"(da), "r"(db), "n"(OFFA / 16), "n"(desc_hi(4096)), "n"(OFFB / 16), "n"(desc_hi(1024)), "n"(ACC));
}
template <int OFFB, int ACC>
__device__ __forceinline__ void wgmma_pv(float (&d)[128], const uint32_t* a, uint32_t db) {
    asm volatile(
        "{\n.reg .b32 lo;\n.reg .b64 b;\nadd.u32 lo, %132, %133;\nmov.b64 b, {lo, %134};\n"
        "wgmma.mma_async.sync.aligned.m64n256k16.f32.bf16.bf16 "
        "{%0, %1, %2, %3, %4, %5, %6, %7, %8, %9, %10, %11, %12, %13, %14, %15, "
        "%16, %17, %18, %19, %20, %21, %22, %23, %24, %25, %26, %27, %28, %29, %30, %31, "
        "%32, %33, %34, %35, %36, %37, %38, %39, %40, %41, %42, %43, %44, %45, %46, %47, "
        "%48, %49, %50, %51, %52, %53, %54, %55, %56, %57, %58, %59, %60, %61, %62, %63, "
        "%64, %65, %66, %67, %68, %69, %70, %71, %72, %73, %74, %75, %76, %77, %78, %79, "
        "%80, %81, %82, %83, %84, %85, %86, %87, %88, %89, %90, %91, %92, %93, %94, %95, "
        "%96, %97, %98, %99, %100, %101, %102, %103, %104, %105, %106, %107, %108, %109, %110, %111, "
        "%112, %113, %114, %115, %116, %117, %118, %119, %120, %121, %122, %123, %124, %125, %126, %127}, "
        "{%128, %129, %130, %131}, b, %135, 1, 1, 1;\n}\n"
        : F32(d, 0), F32(d, 32), F32(d, 64), F32(d, 96)
        : "r"(a[0]), "r"(a[1]), "r"(a[2]), "r"(a[3]), "r"(db), "n"(OFFB / 16), "n"(desc_hi(1024)), "n"(ACC));
}

__device__ __forceinline__ void breathe() { asm volatile("pmevent 0;" ::: "memory"); }
template <int N> __device__ __forceinline__ void pin(float* r) {
#pragma unroll
    for (int i = 0; i < N; i++) asm volatile("" : "+f"(r[i])::"memory");
}

__device__ __forceinline__ float ex2(float x) {
    float y;
    asm("ex2.approx.ftz.f32 %0, %1;" : "=f"(y) : "f"(x));
    return y;
}
__device__ __forceinline__ uint32_t pack_bf16(float lo, float hi) {
    uint32_t r;
    asm("cvt.rn.bf16x2.f32 %0, %1, %2;" : "=r"(r) : "f"(hi), "f"(lo));
    return r;
}

__device__ __forceinline__ bool elect_one() {
    uint32_t p;
    asm volatile("{\n.reg .pred P;\nelect.sync _|P, 0xffffffff;\nselp.u32 %0, 1, 0, P;\n}" : "=r"(p));
    return p;
}

enum { kModeFirst, kModeMid, kModeHold, kModeFlush };

__device__ __forceinline__ uint32_t clock32() {
    uint32_t c;
    asm volatile("mov.u32 %0, %%clock;" : "=r"(c));
    return c;
}
__device__ __forceinline__ void spin(uint32_t t0, uint32_t cycles) {
    while (clock32() - t0 < cycles) __nanosleep(32);
}

__global__ void __launch_bounds__(kThreads, 1)
gqa_attn_kernel(const __grid_constant__ CUtensorMap tmK, const __grid_constant__ CUtensorMap tmV,
                const __grid_constant__ CUtensorMap tmQ64, const __grid_constant__ CUtensorMap tmQ8,
                const __grid_constant__ CUtensorMap tmO, const __grid_constant__ CUtensorMap tmO1) {
    extern __shared__ __align__(1024) uint8_t smem[];
    if (threadIdx.x == 0) {
        asm volatile("prefetch.tensormap [%0];" ::"l"(&tmQ64) : "memory");
        asm volatile("prefetch.tensormap [%0];" ::"l"(&tmK) : "memory");
    }
    const uint32_t sbase = __shfl_sync(0xffffffffu, smem_u32(smem), 0);
    const uint32_t bars = sbase + kOffBar;
    auto BAR = [&](int i) INL { return bars + 8u * i; };

    const int warp = __shfl_sync(0xffffffffu, threadIdx.x >> 5, 0);
    const int lane = threadIdx.x & 31;
    const int triple = blockIdx.x / 3;
    const int sub = blockIdx.x - 3 * triple;
    const int head0 = kTriples - 1 - triple;
    const int nrounds = (head0 + 2 * kTriples < kHeads) ? 3 : 2;
    auto ROW = [&](int r) INL { return (head0 + r * kTriples) * kRowsPerHead + sub * 128; };
    auto XBUF = [&](int r, int k) INL { return sbase + kOffX + ((0x24924u >> (2 * (3 - r + k))) & 3) * 32768u; };

    uint64_t pol;
    asm volatile("createpolicy.fractional.L2::evict_first.b64 %0, 1.0;" : "=l"(pol));
    auto load_kv = [&](int r, int j, int c) INL {
        const int krow = (head0 + r * kTriples) * kSk + j * 128 + (c < 4 ? 0 : (c - 4) * 32);
        const uint32_t f = BAR(kBarKFull + c + (c & 4));
        mbar_expect_tx(f, kChunk);
        const uint32_t dst = c >= 5 && j == 3 && r + 1 == nrounds ? XBUF(r, 2) + (c - 5) * kChunk : sbase + c * kChunk;
        tma_load3(dst, c < 4 ? &tmK : &tmV, f, 0, krow, c < 4 ? c : 0, pol);
    };
    auto load_q = [&](int r, int w) INL {
        mbar_expect_tx(BAR(kBarQFull + w), 32768);
        asm volatile(
            "cp.async.bulk.tensor.4d.shared::cluster.global.mbarrier::complete_tx::bytes.L2::cache_hint [%0], [%1, {%3, %3, %3, %4}], [%2], %5;"
            ::"r"(XBUF(r, w)), "l"(&tmQ64), "r"(BAR(kBarQFull + w)), "r"(0), "r"((ROW(r) + w * 64) / 8), "l"(pol) : "memory");
    };

    uint32_t t_start = 0;
    if (warp == 8) t_start = clock32();
    if (warp == 8 && elect_one()) {
        mbar_init(BAR(kBarQFull), 1);
        mbar_init(BAR(kBarKFull), 1);
        asm volatile("fence.mbarrier_init.release.cluster;" ::: "memory");
        if (nrounds == 2) spin(t_start, kLate1);
        load_q(0, 0);
        load_kv(0, 0, 0);
        breathe();
#pragma unroll
        for (int i = 0; i < 4; i++) {
            if (i) mbar_init(BAR(kBarKFull + i), 1);
            mbar_init(BAR(kBarKEmpty + i), 8);
            mbar_init(BAR(kBarVFull + i), 1);
            mbar_init(BAR(kBarVEmpty + i), 8);
        }
#pragma unroll
        for (int i = 0; i < 2; i++) {
            if (i) mbar_init(BAR(kBarQFull + i), 1);
            mbar_init(BAR(kBarOFull + i), 4);
            mbar_init(BAR(kBarOEmpty + i), 1);
        }
        mbar_init(BAR(kBarQ0Empty), 4);
        asm volatile("fence.mbarrier_init.release.cluster;" ::: "memory");
        load_kv(0, 0, 1);
        load_kv(0, 0, 2);
        load_kv(0, 0, 3);
        load_q(0, 1);
    }
    __syncthreads();

    if (warp >= 8) {
        asm volatile("setmaxnreg.dec.sync.aligned.u32 24;");
        if (warp == 8 && elect_one()) {
            asm volatile("prefetch.tensormap [%0];" ::"l"(&tmV) : "memory");
            asm volatile("prefetch.tensormap [%0];" ::"l"(&tmQ8) : "memory");
            asm volatile("prefetch.tensormap [%0];" ::"l"(&tmO) : "memory");
            asm volatile("prefetch.tensormap [%0];" ::"l"(&tmO1) : "memory");
            int it = 0;
#pragma unroll 1
            for (int r = 0; r < nrounds; r++) {
                if (nrounds == 2 && r == 1) spin(clock32(), kLate2);
                const uint32_t spare = XBUF(r, 2);
                const int orow = ROW(r - 1);
                auto store_o = [&](int half, int g0, int g1) INL {
#pragma unroll
                    for (int g = g0; g < g1; g++) tma_store3(&tmO, spare + g * 4096, 0, orow + g * 16 + half * 8, 0);
                    asm volatile("cp.async.bulk.commit_group;" ::: "memory");
                };
                uint32_t qslots = r + 1 == nrounds ? 0u : r == 0 ? kQSlots0 : kQSlots1;
                uint32_t pslots = r + 1 == nrounds ? 0u : r == 0 ? kPSlots0 : kPSlots1;
                uint32_t qdst = spare;
                int qrow = ROW(r + 1);
                int prow = ROW(r + 1) + (r == 0 ? 64 : 0);
                if (r > 0) {
                    mbar_wait(BAR(kBarQ0Empty), (r & 1) ^ 1);
                    load_q(r, 1);
                }
#pragma unroll 1
                for (int j = 0; j < kTilesKV; j++, it++, qslots >>= 8, pslots >>= 8) {
                    const uint32_t par = (it & 1) ^ 1;
#pragma unroll
                    for (int c = 0; c < 8; c++) {
                        if (it == 0 && c < 4) continue;
                        if (it == 0) spin(t_start, kFirstV + (c - 4) * kFirstVGap);
                        mbar_wait(BAR(kBarKEmpty + c + (c & 4)), par);
                        if (c == 7 && j == 3 && r + 1 == nrounds) mbar_wait(BAR(kBarQ0Empty), r & 1);
                        load_kv(r, j, c);
                        if (c == 0 && j == 1 && qslots) mbar_expect_tx(BAR(kBarQFull), 32768);
                        if ((qslots >> c) & 1) {
                            tma_load3(qdst, &tmQ8, BAR(kBarQFull), 0, qrow, 0, pol);
                            qdst += 4096;
                            qrow += 8;
                        }
                        if ((pslots >> c) & 1) {
                            asm volatile("cp.async.bulk.prefetch.tensor.3d.L2.global [%0, {%1, %2, %1}];"
                                         ::"l"(&tmQ8), "r"(0), "r"(prow) : "memory");
                            prow += 8;
                        }
                        if (c == 7 && r > 0 && j < 2) {
                            mbar_wait(BAR(kBarOFull), j);
                            store_o(j, 0, kOSplit);
                        }
                        if (c == 3 && r > 0 && (j == 1 || j == 2)) {
                            store_o(j - 1, kOSplit, 4);
                            mbar_wait(BAR(kBarOFull + 1), j - 1);
                            store_o(j - 1, 4, 8);
                            asm volatile("cp.async.bulk.wait_group.read 1;" ::: "memory");
                            if (j == 1) mbar_arrive(BAR(kBarOEmpty));
                            asm volatile("cp.async.bulk.wait_group.read 0;" ::: "memory");
                            if (j == 1) mbar_arrive(BAR(kBarOEmpty + 1));
                        }
                    }
                }
            }
        }
    } else {
        asm volatile("setmaxnreg.inc.sync.aligned.u32 240;");
        const int wg = warp >> 2;
        const float kScale = 0.0625f * 1.4426950408889634f;

        const uint32_t descK = desc_lo(sbase + kOffK, 16);
        const uint32_t descV = desc_lo(sbase + kOffV, 4096);

        float o[128];
        float s[64];
        uint32_t p[32];
        float m0, m1, l0, l1, i0 = 0.f, i1 = 0.f;

        auto pack4 = [&](int h, int k, uint32_t* t) INL {
            const float inv = h ? i1 : i0;
#pragma unroll
            for (int b = 0; b < 4; b++)
                t[b] = pack_bf16(o[16 * k + 4 * b + 2 * h] * inv, o[16 * k + 4 * b + 2 * h + 1] * inv);
            asm volatile("" : "+r"(t[0]), "+r"(t[1]), "+r"(t[2]), "+r"(t[3])::"memory");
        };
        auto stage = [&](uint32_t grp, int k, const uint32_t* t) INL {
            asm volatile("stmatrix.sync.aligned.m8n8.x4.shared.b16 [%0], {%1, %2, %3, %4};"
                         ::"r"(grp + (lane & 7) * 128 + (k >> 1) * 1024 + ((((k & 1) * 4 + (lane >> 3)) ^ (lane & 7)) << 4)),
                           "r"(t[0]), "r"(t[1]), "r"(t[2]), "r"(t[3]) : "memory");
        };
        auto hand_over = [&]() INL {
            asm volatile("fence.proxy.async.shared::cta;" ::: "memory");
            __syncwarp();
            mbar_arrive_if(lane == 0, BAR(kBarOFull + wg));
        };
        auto rowmax = [&](float& mx0, float& mx1) INL {
            mx0 = fmaxf(s[0], s[1]);
            mx1 = fmaxf(s[2], s[3]);
#pragma unroll
            for (int i = 4; i < 64; i += 4) {
                mx0 = fmaxf(mx0, fmaxf(s[i], s[i + 1]));
                mx1 = fmaxf(mx1, fmaxf(s[i + 2], s[i + 3]));
            }
            mx0 = fmaxf(mx0, __shfl_xor_sync(0xffffffffu, mx0, 1));
            mx1 = fmaxf(mx1, __shfl_xor_sync(0xffffffffu, mx1, 1));
            mx0 = fmaxf(mx0, __shfl_xor_sync(0xffffffffu, mx0, 2));
            mx1 = fmaxf(mx1, __shfl_xor_sync(0xffffffffu, mx1, 2));
        };
        auto shift = [&](int g) INL {
#pragma unroll
            for (int i = g * 16; i < g * 16 + 16; i += 4) {
                s[i] = fmaf(s[i], kScale, -m0);
                s[i + 1] = fmaf(s[i + 1], kScale, -m0);
                s[i + 2] = fmaf(s[i + 2], kScale, -m1);
                s[i + 3] = fmaf(s[i + 3], kScale, -m1);
            }
        };

        uint32_t held[24];
        uint32_t parked[32];
        auto tile = [&](auto mode, uint32_t descQ, uint32_t descVhi, uint32_t par, bool last, bool flag) INL {
            constexpr bool kFirst = decltype(mode)::value == kModeFirst;
            constexpr bool kHold = decltype(mode)::value == kModeHold;
            constexpr bool kFlush = decltype(mode)::value == kModeFlush;
            constexpr int kPre = kFirst ? kPreFirst : kPreMid;
            constexpr int kSpec = kFirst || kFlush ? 0 : kSpecExp;
            bar_sync(1 + wg, 256);
            static_for<4>([&](auto ci) INL {
                constexpr int c = ci.value;
                mbar_wait(BAR(kBarKFull + c), par);
                wgmma_fence();
                static_for<4>([&](auto ki) INL {
                    constexpr int k = ki.value;
                    wgmma_qk<c * 1024 + k * 32, c * kChunk + k * 32, (c | k) != 0>(s, descQ, descK);
                });
                wgmma_commit();
                if (c == 0 && kFirst && flag) hand_over();
                if (c == 2) {
                    wgmma_wait<2>();
                    if (lane == 0) mbar_arrive(BAR(kBarKEmpty + 0));
                }
            });
            if (wg == 0) bar_arrive(2, 256);
            else if (kFirst) bar_arrive(3, 256);
            wgmma_wait<2>();
            if (lane == 0) mbar_arrive(BAR(kBarKEmpty + 1));
            wgmma_wait<1>();
            if (lane == 0) mbar_arrive(BAR(kBarKEmpty + 2));
            wgmma_wait<0>();
            if (lane == 0) mbar_arrive(BAR(kBarKEmpty + 3));
            if (lane == 0 && last && wg == 0) mbar_arrive(BAR(kBarQ0Empty));
            reg_fence(s);

            float e[kSpecExp];
            if (kFirst) {
                int c0 = max(__float_as_int(s[0]), __float_as_int(s[1]));
                int c1 = max(__float_as_int(s[2]), __float_as_int(s[3]));
#pragma unroll
                for (int i = 4; i < 64; i += 4) {
                    c0 = __vimax3_s32(c0, __float_as_int(s[i]), __float_as_int(s[i + 1]));
                    c1 = __vimax3_s32(c1, __float_as_int(s[i + 2]), __float_as_int(s[i + 3]));
                }
                c0 = max(c0, __shfl_xor_sync(0xffffffffu, c0, 1));
                c1 = max(c1, __shfl_xor_sync(0xffffffffu, c1, 1));
                c0 = max(c0, __shfl_xor_sync(0xffffffffu, c0, 2));
                c1 = max(c1, __shfl_xor_sync(0xffffffffu, c1, 2));
                float mx0 = __int_as_float(c0), mx1 = __int_as_float(c1);
                if (__any_sync(0xffffffffu, (c0 | c1) < 0)) rowmax(mx0, mx1);
                m0 = mx0 * kScale;
                m1 = mx1 * kScale;
                l0 = l1 = 0.f;
            } else {
                int c0 = 0, c1 = 0;
#pragma unroll
                for (int g = 0; g < 5; g++) {
                    if (g < 4) shift(g);
                    if (g > 0) {
#pragma unroll
                        for (int i = g * 16 - 16; i < g * 16; i += 4) {
                            c0 = __vimax3_s32(c0, __float_as_int(s[i]), __float_as_int(s[i + 1]));
                            c1 = __vimax3_s32(c1, __float_as_int(s[i + 2]), __float_as_int(s[i + 3]));
                        }
#pragma unroll
                        for (int i = (g - 1) * kSpec / 4; i < g * kSpec / 4; i++) e[i] = ex2(s[i]);
                    }
                    if (g > 0 && g < 4) {
                        reg_fence(s);
                        asm volatile("" : "+r"(c0), "+r"(c1)::"memory");
                        if (kSpec) pin<kSpecExp / 4>(&e[(g - 1) * kSpecExp / 4]);
                        breathe();
                        reg_fence(s);
                    }
                }
                if (__any_sync(0xffffffffu, max(c0, c1) > 0x41000000)) {
                    float d0, d1;
                    rowmax(d0, d1);
                    const float n0 = m0 + fmaxf(d0, 0.f), n1 = m1 + fmaxf(d1, 0.f);
                    d0 = n0 - m0;
                    d1 = n1 - m1;
                    const float a0 = ex2(-d0), a1 = ex2(-d1);
                    m0 = n0; m1 = n1; l0 *= a0; l1 *= a1;
#pragma unroll
                    for (int i = 0; i < 64; i += 4) {
                        s[i] -= d0; s[i + 1] -= d0; s[i + 2] -= d1; s[i + 3] -= d1;
                    }
#pragma unroll
                    for (int i = 0; i < kSpec; i++) e[i] = ex2(s[i]);
                    if (kFlush) {
                        breathe();
#pragma unroll
                        for (int i = 0; i < 24; i++) {
                            const float a = (i & 1) ? a1 : a0;
                            held[i] = pack_bf16(__uint_as_float(held[i] << 16) * a, __uint_as_float(held[i] & 0xffff0000u) * a);
                            if (i & 1) {
                                reg_fence(held);
                                breathe();
                                reg_fence(held);
                            }
                        }
                    }
#pragma unroll
                    for (int i = 0; i < 128; i += 4) {
                        o[i] *= a0; o[i + 1] *= a0; o[i + 2] *= a1; o[i + 3] *= a1;
                    }
                }
            }
            auto expchunk = [&](int c) INL {
                if (kFirst) shift(c);
#pragma unroll
                for (int i = c * 16; i < c * 16 + 16; i += 4) {
                    const float e0 = i < kSpec ? e[i < kSpec ? i : 0] : ex2(s[i]);
                    const float e1 = i < kSpec ? e[i < kSpec ? i + 1 : 0] : ex2(s[i + 1]);
                    const float e2 = i < kSpec ? e[i < kSpec ? i + 2 : 0] : ex2(s[i + 2]);
                    const float e3 = i < kSpec ? e[i < kSpec ? i + 3 : 0] : ex2(s[i + 3]);
                    l0 += e0 + e1;
                    l1 += e2 + e3;
                    p[i / 2] = pack_bf16(e0, e1);
                    p[i / 2 + 1] = pack_bf16(e2, e3);
                }
            };
#pragma unroll
            for (int c = 0; c < kPre; c++) expchunk(c);

            if (kHold) {
                mbar_wait(BAR(kBarVFull), par);
                bar_sync(4, 256);
                wgmma_fence();
                wgmma_pv<0, 1>(o, &p[0], descV);
                wgmma_pv<2048, 1>(o, &p[4], descV);
                wgmma_commit();
                bar_arrive(1, 256);
#pragma unroll
                for (int c = 1; c < 4; c++) {
                    mbar_wait(BAR(kBarVFull + c), par);
                    __syncwarp();
                    if (lane == 0) mbar_arrive(BAR(kBarVEmpty + c));
                }
                expchunk(2);
                expchunk(3);
#pragma unroll
                for (int i = 16; i < 32; i++) asm volatile("" : "+r"(p[i])::"memory");
                breathe();
                wgmma_wait<0>();
                if (lane == 0) mbar_arrive(BAR(kBarVEmpty));
#pragma unroll
                for (int i = 0; i < 24; i++) held[i] = p[8 + i];
                reg_fence(held);
                reg_fence(o);
                return;
            }
            static_for<4>([&](auto ci) INL {
                constexpr int c = ci.value;
                mbar_wait(BAR(kBarVFull + c), par);
                if (c == 0 && kFirst && wg == 0) bar_sync(3, 256);
                if (c == 0 && kFlush) {
#pragma unroll
                    for (int i = 16; i < 24; i++) held[i] *= gridDim.y;
                    bar_sync(4, 256);
                    wgmma_fence();
                    static_for<6>([&](auto ki) INL {
                        constexpr int k = ki.value;
                        wgmma_pv<(1 + k / 2) * kChunk + (k & 1) * 2048, 1>(o, &held[4 * k], descV);
                    });
                    breathe();
                    reg_fence(s);
#pragma unroll
                    for (int x = kPre; x < 4; x++) expchunk(x);
                    reg_fence(p);
                    breathe();
                }
                wgmma_fence();
                wgmma_pv<c * kChunk, !kFirst || c != 0>(o, &p[c * 8], c == 0 ? descV : descVhi);
                wgmma_pv<c * kChunk + 2048, 1>(o, &p[c * 8 + 4], c == 0 ? descV : descVhi);
                wgmma_commit();
                if (!kFlush && c + 1 >= kPre && c + 1 < 4) expchunk(c + 1);
            });
            if (wg == 1) bar_arrive(1, 256);
            else if (!kFirst && flag) bar_arrive(4, 256);
            if (last) {
                l0 += __shfl_xor_sync(0xffffffffu, l0, 1);
                l1 += __shfl_xor_sync(0xffffffffu, l1, 1);
                l0 += __shfl_xor_sync(0xffffffffu, l0, 2);
                l1 += __shfl_xor_sync(0xffffffffu, l1, 2);
                i0 = __fdividef(1.f, l0);
                i1 = __fdividef(1.f, l1);
                mbar_wait(BAR(kBarKEmpty + 3), 1);
            }
            wgmma_wait<3>();
            if (lane == 0) mbar_arrive(BAR(kBarVEmpty + 0));
            wgmma_wait<2>();
            if (lane == 0) mbar_arrive(BAR(kBarVEmpty + 1));
            wgmma_wait<1>();
            if (lane == 0) mbar_arrive(BAR(kBarVEmpty + 2));
            wgmma_wait<0>();
            if (lane == 0) mbar_arrive(BAR(kBarVEmpty + 3));
            reg_fence(o);
            reg_fence(p);
        };

#pragma unroll
        for (int i = 0; i < 128; i++) o[i] = 0.f;
        if (wg == 1) bar_arrive(1, 256);
        const uint32_t descVend = desc_lo(XBUF(nrounds - 1, 2) - kChunk, 4096);
#pragma unroll 1
        for (int r = 0; r < nrounds; r++) {
            if (r > 0) {
#pragma unroll
                for (int k = 0; k < 8; k++) {
                    uint32_t t[4];
                    pack4(0, k, t);
                    pack4(1, k, &parked[4 * k]);
                    breathe();
                    stage(XBUF(r, 2) + warp * 4096, k, t);
                    if (k < 7) pin<16>(&o[16 * k + 16]);
                }
            } else {
                breathe();
#pragma unroll
                for (int i = 0; i < 32; i++) asm volatile("mov.u32 %0, 0;" : "=r"(parked[i]));
            }
            const uint32_t descQ = desc_lo(XBUF(r, wg), 16);
            mbar_wait(BAR(kBarQFull + wg), r & 1);
            tile(Int<kModeFirst>(), descQ, descV, 0, false, r > 0);
            if (r > 0) {
                mbar_wait(BAR(kBarOEmpty + wg), (r - 1) & 1);
#pragma unroll
                for (int k = 0; k < 8; k++) stage(XBUF(r, 2) + warp * 4096, k, &parked[4 * k]);
                hand_over();
            }
            const bool fin = r + 1 == nrounds;
            const int jend = fin && wg == 1 ? 2 : kTilesKV;
#pragma unroll 1
            for (int j = 1; j < jend; j++) {
                const bool last = j == kTilesKV - 1;
                tile(Int<kModeMid>(), descQ, last && fin ? descVend : descV, j & 1, last, fin && j >= 2);
            }
        }
        const int r = nrounds - 1;
        if (wg == 1) {
            tile(Int<kModeHold>(), desc_lo(XBUF(r, 1), 16), descV, 0, false, true);
            tile(Int<kModeFlush>(), desc_lo(XBUF(r, 1), 16), descVend, 1, true, true);
        }
        const uint32_t grp = sbase + kOffK + warp * 8192;
        const int orow = ROW(r) + warp * 16;
        auto send = [&](const CUtensorMap* map, int h, int blk) INL {
            asm volatile("fence.proxy.async.shared::cta;" ::: "memory");
            __syncwarp();
            if (elect_one()) tma_store3(map, grp + h * 4096 + blk * 1024, 0, orow + h * 8, blk);
        };
#pragma unroll
        for (int h = 0; h < 2; h++) {
#pragma unroll
            for (int k = 0; k < 8; k += 2) {
                uint32_t t[8];
                pack4(h, k, t);
                pack4(h, k + 1, t + 4);
                breathe();
                stage(grp + h * 4096, k, t);
                stage(grp + h * 4096, k + 1, t + 4);
                if (h == 0 && k != 4) {
                    send(&tmO1, 0, k >> 1);
                    if (k == 6 && elect_one()) tma_store3(&tmO1, grp + 2048, 0, orow, 2);
                    breathe();
                }
                if (k < 6) pin<32>(&o[16 * k + 32]);
            }
            if (h == 1) send(&tmO, 1, 0);
        }
        asm volatile("cp.async.bulk.commit_group;" ::: "memory");
        asm volatile("cp.async.bulk.wait_group.read 0;" ::: "memory");
        if (wg == 0) bar_sync(1, 256);
    }
}

typedef CUresult (*EncodeFn)(CUtensorMap*, CUtensorMapDataType, cuuint32_t, void*, const cuuint64_t*, const cuuint64_t*,
                             const cuuint32_t*, const cuuint32_t*, CUtensorMapInterleave, CUtensorMapSwizzle,
                             CUtensorMapL2promotion, CUtensorMapFloatOOBfill);

void make_map(EncodeFn fn, CUtensorMap* m, const void* ptr, uint64_t rows, uint32_t box_rows, uint32_t nblk) {
    cuuint64_t dims[3] = {64, rows, 4};
    cuuint64_t strides[2] = {kD * 2, 128};
    cuuint32_t box[3] = {64, box_rows, nblk};
    cuuint32_t estr[3] = {1, 1, 1};
    fn(m, CU_TENSOR_MAP_DATA_TYPE_BFLOAT16, 3, const_cast<void*>(ptr), dims, strides, box, estr,
       CU_TENSOR_MAP_INTERLEAVE_NONE, CU_TENSOR_MAP_SWIZZLE_128B, CU_TENSOR_MAP_L2_PROMOTION_L2_128B,
       CU_TENSOR_MAP_FLOAT_OOB_FILL_NONE);
}

void make_map8(EncodeFn fn, CUtensorMap* m, const void* ptr, uint64_t rows) {
    cuuint64_t dims[4] = {64, 8, 4, rows / 8};
    cuuint64_t strides[3] = {kD * 2, 128, kD * 16};
    cuuint32_t box[4] = {64, 8, 4, 8};
    cuuint32_t estr[4] = {1, 1, 1, 1};
    fn(m, CU_TENSOR_MAP_DATA_TYPE_BFLOAT16, 4, const_cast<void*>(ptr), dims, strides, box, estr,
       CU_TENSOR_MAP_INTERLEAVE_NONE, CU_TENSOR_MAP_SWIZZLE_128B, CU_TENSOR_MAP_L2_PROMOTION_L2_128B,
       CU_TENSOR_MAP_FLOAT_OOB_FILL_NONE);
}

}

extern "C" void kernel_launch(void* const* d_in, const int* in_sizes, int n_in, void* d_out, int out_size) {
    (void)in_sizes; (void)n_in; (void)out_size;
    static EncodeFn encode = nullptr;
    if (!encode) {
        void* fn = nullptr;
        cudaDriverEntryPointQueryResult st;
        cudaGetDriverEntryPoint("cuTensorMapEncodeTiled", &fn, cudaEnableDefault, &st);
        encode = (EncodeFn)fn;
        cudaFuncSetAttribute(gqa_attn_kernel, cudaFuncAttributeMaxDynamicSharedMemorySize, kSmemBytes);
    }
    CUtensorMap tmK, tmV, tmQ64, tmQ8, tmO, tmO1;
    make_map(encode, &tmK, d_in[1], (uint64_t)kHeads * kSk, 128, 1);
    make_map(encode, &tmV, d_in[2], (uint64_t)kHeads * kSk, 32, 4);
    make_map8(encode, &tmQ64, d_in[0], (uint64_t)kHeads * kRowsPerHead);
    make_map(encode, &tmQ8, d_in[0], (uint64_t)kHeads * kRowsPerHead, 8, 4);
    make_map(encode, &tmO, d_out, (uint64_t)kHeads * kRowsPerHead, 8, 4);
    make_map(encode, &tmO1, d_out, (uint64_t)kHeads * kRowsPerHead, 8, 1);
    gqa_attn_kernel<<<kGrid, kThreads, kSmemBytes>>>(tmK, tmV, tmQ64, tmQ8, tmO, tmO1);
}
```
